```python
import torch

def _softmax(x, axis=-1):
    return torch.softmax(x, dim=axis)
def _gelu(x):
    return torch.nn.functional.gelu(x, approximate="tanh")
def _silu(x):
    return torch.nn.functional.silu(x)
def _sigmoid(x):
    return torch.sigmoid(x)
def _layernorm(x, axis=-1, eps=1e-5):
    m = x.mean(dim=axis, keepdim=True)
    v = x.var(dim=axis, keepdim=True, unbiased=False)
    return (x - m) / torch.sqrt(v + eps)
def _scatter_add(tgt, idx, src, axis=0):
    return tgt.clone().index_add_(axis, idx, src)
def _segment_sum(src, seg, n):
    out = torch.zeros((n,) + src.shape[1:], dtype=src.dtype)
    return out.index_add_(0, seg, src)
def _pad(x, pw):
    flat = tuple(v for pair in reversed(pw) for v in pair)
    return torch.nn.functional.pad(x, flat)

kernel_name = 'standalone__gqa_softmax__near_ridge'

def setup_inputs():

    _w = (lambda a: (lambda t: t.to(torch.bfloat16) if t.is_floating_point() else t)(torch.as_tensor(a)))
    B, Hq, Hkv, Sq, Sk, D = 16, 32, 16, 512, 512, 128
    return {
        "q": _w((lambda *s: torch.randn(*s, dtype=torch.bfloat16) * 0.8)(B, Hq, Sq, D)),
        "k": _w((lambda *s: torch.randn(*s, dtype=torch.bfloat16) * 0.8)(B, Hkv, Sk, D)),
        "v": _w((lambda *s: torch.randn(*s, dtype=torch.bfloat16) * 0.05)(B, Hkv, Sk, D)),
    }

def reference(q, k, v):
    B, Hq, Sq, D = q.shape
    Hkv = k.shape[1]
    rep = Hq // Hkv
    k = (lambda x, n, axis: torch.repeat_interleave(x, n, dim=axis))(k, rep, axis=1)
    v = (lambda x, n, axis: torch.repeat_interleave(x, n, dim=axis))(v, rep, axis=1)
    scale = D ** -0.5
    scores = torch.einsum("bhqd,bhkd->bhqk", q, k) * scale
    p = _softmax(scores, axis=-1)
    return torch.einsum("bhqk,bhkd->bhqd", p, v)
```

```cpp
#include <cuda_runtime.h>
#include <cuda_bf16.h>
#include <cuda.h>
#include <stdint.h>

#define SCHED 1

namespace {

constexpr int NCTA = 128;
constexpr int NT   = 16;
constexpr int BLK_BYTES = 32768;

constexpr uint64_t PH_START = 0xEECCAA8866442200ull, PH_LOG = 0x1111111111111111ull;
constexpr uint32_t mk_first() { uint32_t m = 0; for (int i = 0; i < NT; i++) if ((int)((PH_START >> (4 * i)) & 15) == i) m |= 1u << i; return m; }
constexpr uint32_t FIRST_MASK = mk_first();
constexpr uint32_t LAST_MASK = (FIRST_MASK >> 1) | (1u << (NT - 1));

constexpr uint32_t SM_K = 0;
constexpr uint32_t SM_V = 3 * BLK_BYTES;
constexpr uint32_t SM_Q = 6 * BLK_BYTES;
constexpr uint32_t SM_BAR = 7 * BLK_BYTES;
constexpr uint32_t SM_TOTAL = SM_BAR + 256 + 1024;
constexpr uint32_t B_KFULL = 0, B_KEMPTY = 24, B_VFULL = 48, B_VEMPTY = 72, B_QFULL = 96, B_QREL = 112, B_DONE = 128;

__device__ __forceinline__ uint32_t smem_u32(const void* p) { return (uint32_t)__cvta_generic_to_shared(p); }
__device__ __forceinline__ void mbar_init(uint32_t bar, uint32_t cnt) { asm volatile("mbarrier.init.shared::cta.b64 [%0], %1;" ::"r"(bar), "r"(cnt)); }
__device__ __forceinline__ void mbar_arrive(uint32_t bar) { asm volatile("mbarrier.arrive.shared::cta.b64 _, [%0];" ::"r"(bar) : "memory"); }
__device__ __forceinline__ void mbar_expect_tx(uint32_t bar, uint32_t bytes) { asm volatile("mbarrier.arrive.expect_tx.shared::cta.b64 _, [%0], %1;" ::"r"(bar), "r"(bytes) : "memory"); }
__device__ __forceinline__ bool mbar_try(uint32_t bar, uint32_t parity) {
    uint32_t ok;
    asm volatile("{.reg .pred p; mbarrier.try_wait.parity.shared::cta.b64 p, [%1], %2; selp.u32 %0,1,0,p;}" : "=r"(ok) : "r"(bar), "r"(parity) : "memory");
    return ok;
}
__device__ __forceinline__ void mbar_wait_b(uint32_t bar, uint32_t parity) {
#pragma unroll 1
    for (int i = 0; i < (1 << 22); i++) { if (mbar_try(bar, parity)) return; }
    __trap();
}
__device__ __forceinline__ void mbar_wait(uint32_t bar, uint32_t parity) {
    asm volatile("{\n.reg .pred p;\nLAB_WAIT:\nmbarrier.try_wait.parity.shared::cta.b64 p, [%0], %1;\n@!p bra LAB_WAIT;\n}" ::"r"(bar), "r"(parity) : "memory");
}
__device__ __forceinline__ void tma_load(uint32_t dst, const CUtensorMap* tm, int c0, int c1, uint32_t bar) {
    asm volatile("cp.async.bulk.tensor.2d.shared::cluster.global.mbarrier::complete_tx::bytes [%0], [%1, {%3, %4}], [%2];"
                 ::"r"(dst), "l"(tm), "r"(bar), "r"(c0), "r"(c1) : "memory");
}
__device__ __forceinline__ void tma_store(uint32_t src, const CUtensorMap* tm, int c0, int c1) {
    asm volatile("cp.async.bulk.tensor.2d.global.shared::cta.bulk_group [%1, {%2, %3}], [%0];"
                 ::"r"(src), "l"(tm), "r"(c0), "r"(c1) : "memory");
}
__device__ __forceinline__ void bar_sync(int id, int n) { asm volatile("bar.sync %0, %1;" ::"r"(id), "r"(n) : "memory"); }
__device__ __forceinline__ void bar_arrive(int id, int n) { asm volatile("bar.arrive %0, %1;" ::"r"(id), "r"(n) : "memory"); }
__device__ __forceinline__ void wg_fence() { asm volatile("wgmma.fence.sync.aligned;" ::: "memory"); }
__device__ __forceinline__ void wg_commit() { asm volatile("wgmma.commit_group.sync.aligned;" ::: "memory"); }
template <int N> __device__ __forceinline__ void wg_wait() { asm volatile("wgmma.wait_group.sync.aligned %0;" ::"n"(N) : "memory"); }

__device__ __forceinline__ uint64_t mkdesc(uint32_t addr, uint32_t lbo, uint32_t sbo) {
    uint64_t d = 0;
    d |= (uint64_t)((addr & 0x3FFFF) >> 4);
    d |= (uint64_t)((lbo & 0x3FFFF) >> 4) << 16;
    d |= (uint64_t)((sbo & 0x3FFFF) >> 4) << 32;
    d |= (uint64_t)1 << 62;
    return d;
}

#define R8(d, o) "+f"(d[o + 0]), "+f"(d[o + 1]), "+f"(d[o + 2]), "+f"(d[o + 3]), "+f"(d[o + 4]), "+f"(d[o + 5]), "+f"(d[o + 6]), "+f"(d[o + 7])
#define R64(d) R8(d, 0), R8(d, 8), R8(d, 16), R8(d, 24), R8(d, 32), R8(d, 40), R8(d, 48), R8(d, 56)
#define D64 "{%0,%1,%2,%3,%4,%5,%6,%7,%8,%9,%10,%11,%12,%13,%14,%15,%16,%17,%18,%19,%20,%21,%22,%23,%24,%25,%26,%27,%28,%29,%30,%31,%32,%33,%34,%35,%36,%37,%38,%39,%40,%41,%42,%43,%44,%45,%46,%47,%48,%49,%50,%51,%52,%53,%54,%55,%56,%57,%58,%59,%60,%61,%62,%63}"

template <int TB>
__device__ __forceinline__ void wgmma_rs(float (&d)[64], uint32_t a0, uint32_t a1, uint32_t a2, uint32_t a3, uint64_t db, int scale_d) {
    asm volatile("{.reg .pred p; setp.ne.b32 p, %69, 0;\n"
                 "wgmma.mma_async.sync.aligned.m64n128k16.f32.bf16.bf16 " D64 ", {%64,%65,%66,%67}, %68, p, 1, 1, %70;}\n"
                 : R64(d) : "r"(a0), "r"(a1), "r"(a2), "r"(a3), "l"(db), "r"(scale_d), "n"(TB));
}
__device__ __forceinline__ void fence_regs(float (&d)[64]) { asm volatile("" : R64(d)::"memory"); }
__device__ __forceinline__ void fence_regs(uint32_t (&d)[32]) {
#pragma unroll
    for (int i = 0; i < 32; i++) asm volatile("" : "+r"(d[i])::"memory");
}
__device__ __forceinline__ float ex2(float x) { float y; asm("ex2.approx.ftz.f32 %0, %1;" : "=f"(y) : "f"(x)); return y; }
__device__ __forceinline__ uint32_t pack_bf16(float lo, float hi) { uint32_t r; asm("cvt.rn.bf16x2.f32 %0, %1, %2;" : "=r"(r) : "f"(hi), "f"(lo)); return r; }
__device__ __forceinline__ void ldsm4(uint32_t addr, uint32_t& a, uint32_t& b, uint32_t& c, uint32_t& d) {
    asm volatile("ldmatrix.sync.aligned.m8n8.x4.shared.b16 {%0,%1,%2,%3}, [%4];" : "=r"(a), "=r"(b), "=r"(c), "=r"(d) : "r"(addr) : "memory");
}
__device__ __forceinline__ void stsm4(uint32_t addr, uint32_t a, uint32_t b, uint32_t c, uint32_t d) {
    asm volatile("stmatrix.sync.aligned.m8n8.x4.shared.b16 [%4], {%0,%1,%2,%3};" ::"r"(a), "r"(b), "r"(c), "r"(d), "r"(addr) : "memory");
}

__device__ __forceinline__ int tile_head(int t, int cta) {
    int st = (PH_START >> (4 * t)) & 15, lg = (PH_LOG >> (4 * t)) & 15;
    return 16 * st + (cta >> (3 - lg));
}
__device__ __forceinline__ int tile_qrow(int t, int cta) {
    int st = (PH_START >> (4 * t)) & 15, lg = (PH_LOG >> (4 * t)) & 15;
    int head = 16 * st + (cta >> (3 - lg));
    int qt = ((cta & ((8 >> lg) - 1)) << lg) + (t - st);
    return head * 1024 + qt * 128;
}

constexpr float SCALE_LOG2 = 0.08838834764831845f * 1.4426950408889634f;

#define TS(i)

struct Consumer {
    float S[64], O[64];
    uint32_t P[32], Q[32];
    float m0, m1, l0, l1, lp0, lp1;
    uint32_t sb, qaddr;
    uint32_t kph, vph;
    int wg, lane;

    __device__ __forceinline__ void load_q() {
#pragma unroll
        for (int s = 0; s < 8; s++) ldsm4((qaddr ^ ((s & 3) << 5)) + (s >> 2) * 8192, Q[4 * s], Q[4 * s + 1], Q[4 * s + 2], Q[4 * s + 3]);
    }
    __device__ __forceinline__ void issue_qk(int slot) {
        uint64_t dk = mkdesc(sb + SM_K + slot * BLK_BYTES, 16, 1024);
#pragma unroll
        for (int k = 0; k < 8; k++) wgmma_rs<0>(S, Q[4 * k], Q[4 * k + 1], Q[4 * k + 2], Q[4 * k + 3], dk + ((k >> 2) * 1024 + (k & 3) * 2), k != 0);
        wg_commit();
    }
    __device__ __forceinline__ void issue_pv(int slot, int acc) {
        uint64_t dv = mkdesc(sb + SM_V + slot * BLK_BYTES, 16384, 1024);
#pragma unroll
        for (int k = 0; k < 8; k++) wgmma_rs<1>(O, P[4 * k], P[4 * k + 1], P[4 * k + 2], P[4 * k + 3], dv + k * 128, k != 0 || acc);
        wg_commit();
    }
    template <bool FIRST>
    __device__ __forceinline__ void softmax(float& a0, float& a1) {
        float x0 = fmaxf(S[0], S[1]), x1 = fmaxf(S[2], S[3]);
        float y0 = fmaxf(S[4], S[5]), y1 = fmaxf(S[6], S[7]);
#pragma unroll
        for (int i = 2; i < 16; i += 2) {
            x0 = fmaxf(x0, fmaxf(S[4 * i], S[4 * i + 1]));
            x1 = fmaxf(x1, fmaxf(S[4 * i + 2], S[4 * i + 3]));
            y0 = fmaxf(y0, fmaxf(S[4 * i + 4], S[4 * i + 5]));
            y1 = fmaxf(y1, fmaxf(S[4 * i + 6], S[4 * i + 7]));
        }
        x0 = fmaxf(x0, y0); x1 = fmaxf(x1, y1);
        x0 = fmaxf(x0, __shfl_xor_sync(0xffffffffu, x0, 1));
        x1 = fmaxf(x1, __shfl_xor_sync(0xffffffffu, x1, 1));
        x0 = fmaxf(x0, __shfl_xor_sync(0xffffffffu, x0, 2));
        x1 = fmaxf(x1, __shfl_xor_sync(0xffffffffu, x1, 2));
        x0 *= SCALE_LOG2; x1 *= SCALE_LOG2;
        if (FIRST) {
            lp0 = l0; lp1 = l1;
            m0 = x0; m1 = x1;
        } else {
            x0 = fmaxf(x0, m0); x1 = fmaxf(x1, m1);
            a0 = ex2(m0 - x0); a1 = ex2(m1 - x1);
            m0 = x0; m1 = x1;
        }
        float s0 = 0.f, s1 = 0.f, t0 = 0.f, t1 = 0.f;
#pragma unroll
        for (int i = 0; i < 16; i++) {
            S[4 * i]     = ex2(fmaf(S[4 * i],     SCALE_LOG2, -x0));
            S[4 * i + 1] = ex2(fmaf(S[4 * i + 1], SCALE_LOG2, -x0));
            S[4 * i + 2] = ex2(fmaf(S[4 * i + 2], SCALE_LOG2, -x1));
            S[4 * i + 3] = ex2(fmaf(S[4 * i + 3], SCALE_LOG2, -x1));
            s0 += S[4 * i]; t0 += S[4 * i + 1];
            s1 += S[4 * i + 2]; t1 += S[4 * i + 3];
        }
        if (FIRST) { l0 = s0 + t0; l1 = s1 + t1; }
        else { l0 = fmaf(l0, a0, s0 + t0); l1 = fmaf(l1, a1, s1 + t1); }
    }
    __device__ __forceinline__ void make_p() {
#pragma unroll
        for (int i = 0; i < 32; i++) P[i] = pack_bf16(S[2 * i], S[2 * i + 1]);
    }
    __device__ __forceinline__ void rescale(float a0, float a1) {
#pragma unroll
        for (int i = 0; i < 16; i++) { O[4 * i] *= a0; O[4 * i + 1] *= a0; O[4 * i + 2] *= a1; O[4 * i + 3] *= a1; }
    }
    __device__ __forceinline__ void epilogue(float e0, float e1) {
        e0 += __shfl_xor_sync(0xffffffffu, e0, 1); e1 += __shfl_xor_sync(0xffffffffu, e1, 1);
        e0 += __shfl_xor_sync(0xffffffffu, e0, 2); e1 += __shfl_xor_sync(0xffffffffu, e1, 2);
        float r0 = __frcp_rn(e0), r1 = __frcp_rn(e1);
#pragma unroll
        for (int s = 0; s < 8; s++) {
            uint32_t a = pack_bf16(O[8 * s] * r0, O[8 * s + 1] * r0), b = pack_bf16(O[8 * s + 2] * r1, O[8 * s + 3] * r1);
            uint32_t c = pack_bf16(O[8 * s + 4] * r0, O[8 * s + 5] * r0), d = pack_bf16(O[8 * s + 6] * r1, O[8 * s + 7] * r1);
            stsm4((qaddr ^ ((s & 3) << 5)) + (s >> 2) * 8192, a, b, c, d);
        }
        asm volatile("fence.proxy.async.shared::cta;" ::: "memory");
        __syncwarp();
        if (lane == 0) mbar_arrive(sb + SM_BAR + B_QREL + 8 * wg);
    }
    __device__ __forceinline__ void wait_k(int slot, bool fresh) { kph ^= (uint32_t)fresh << slot; mbar_wait(sb + SM_BAR + B_KFULL + 8 * slot, (kph >> slot) & 1); }
    __device__ __forceinline__ void wait_v(int slot, bool fresh) { vph ^= (uint32_t)fresh << slot; mbar_wait(sb + SM_BAR + B_VFULL + 8 * slot, (vph >> slot) & 1); }
    __device__ __forceinline__ void rel_k(int slot) { if (lane == 0) mbar_arrive(sb + SM_BAR + B_KEMPTY + 8 * slot); }
    __device__ __forceinline__ void rel_v(int slot) { if (lane == 0) mbar_arrive(sb + SM_BAR + B_VEMPTY + 8 * slot); }

    template <int J>
    __device__ __forceinline__ void step(int ks, bool krel, int vs, bool vrel, int nks, bool nkfresh, bool nvfresh, bool nextq, int qph) {
        bar_sync(1 + wg, 256);
        TS(0);
        wg_fence();
        issue_qk(ks);
        issue_pv(vs, J != 1);
        bar_arrive(2 - wg, 256);
        TS(1);
        wg_wait<1>();
        fence_regs(S);
        TS(2);
        if (krel) rel_k(ks);
        if (J == 3 && nextq) {
            fence_regs(Q);
            mbar_wait(sb + SM_BAR + B_QFULL + 8 * wg, qph);
            load_q();
        }
        float a0, a1;
        softmax<J == 0>(a0, a1);
        fence_regs(S);
        TS(3);
        wait_k(nks, nkfresh);
        wg_wait<0>();
        fence_regs(O);
        fence_regs(S);
        TS(4);
        if (vrel) rel_v(vs);
        make_p();
        if (J == 0) epilogue(lp0, lp1);
        else rescale(a0, a1);
        fence_regs(O);
        fence_regs(P);
        wait_v(ks, nvfresh);
        TS(5);
    }
};

__global__ void __launch_bounds__(384, 1)
gqa_fwd_kernel(const __grid_constant__ CUtensorMap tmQ, const __grid_constant__ CUtensorMap tmK,
               const __grid_constant__ CUtensorMap tmV, const __grid_constant__ CUtensorMap tmO) {
    extern __shared__ char smem_raw[];
    const uint32_t sb = (smem_u32(smem_raw) + 1023) & ~1023u;
    const uint32_t bars = sb + SM_BAR;
    const int warp = __shfl_sync(0xffffffffu, threadIdx.x >> 5, 0);
    const int lane = threadIdx.x & 31;
    const int cta = blockIdx.x;

    if (threadIdx.x == 0) {
        for (int i = 0; i < 3; i++) {
            mbar_init(bars + B_KFULL + 8 * i, 1); mbar_init(bars + B_KEMPTY + 8 * i, 8);
            mbar_init(bars + B_VFULL + 8 * i, 1); mbar_init(bars + B_VEMPTY + 8 * i, 8);
        }
        for (int i = 0; i < 2; i++) { mbar_init(bars + B_QFULL + 8 * i, 1); mbar_init(bars + B_QREL + 8 * i, 4); }
        mbar_init(bars + B_DONE, 8);
        asm volatile("fence.mbarrier_init.release.cluster;" ::: "memory");
    }
    __syncthreads();

    if (warp >= 8) {
        asm volatile("setmaxnreg.dec.sync.aligned.u32 24;");
        if (lane == 0) {
            if (warp < 10) {
                const CUtensorMap* tm = warp == 8 ? &tmK : &tmV;
                const uint32_t buf = sb + (warp == 8 ? SM_K : SM_V);
                const uint32_t full = bars + (warp == 8 ? B_KFULL : B_VFULL), empty = bars + (warp == 8 ? B_KEMPTY : B_VEMPTY);
                uint32_t eph = 7;
                int base = 0, flip = 0;
                for (int t = 0; t < NT; t++) {
                    const int row = tile_head(t, cta) * 512;
                    const bool first = (FIRST_MASK >> t) & 1;
                    if (first) flip = 0;
                    for (int j = first ? 0 : 3; j < 4; j++) {
                        int slot = base + j; if (slot >= 3) slot -= 3;
                        const int blk = (j == 3 && flip) ? 0 : j;
                        mbar_wait_b(empty + 8 * slot, (eph >> slot) & 1); eph ^= 1u << slot;
                        mbar_expect_tx(full + 8 * slot, BLK_BYTES);
                        tma_load(buf + slot * BLK_BYTES, tm, 0, row + blk * 128, full + 8 * slot);
                        tma_load(buf + slot * BLK_BYTES + 16384, tm, 64, row + blk * 128, full + 8 * slot);
                    }
                    flip ^= 1;
                    if ((LAST_MASK >> t) & 1) base = base == 2 ? 0 : base + 1;
                }
                if (warp == 8) mbar_wait_b(bars + B_DONE, 0);
            } else {
                const int w = warp - 10;
                const uint32_t buf = sb + SM_Q + w * 16384;
                const uint32_t full = bars + B_QFULL + 8 * w, rel = bars + B_QREL + 8 * w;
                for (int t = -2; t < NT; t++) {
                    if (t >= -1) mbar_wait_b(rel, (t + 1) & 1);
                    if (t >= 0) {
                        const int row = tile_qrow(t, cta) + w * 64;
                        tma_store(buf, &tmO, 0, row);
                        tma_store(buf + 8192, &tmO, 64, row);
                        asm volatile("cp.async.bulk.commit_group;" ::: "memory");
                        asm volatile("cp.async.bulk.wait_group.read 0;" ::: "memory");
                    }
                    if (t + 2 < NT) {
                        const int row = tile_qrow(t + 2, cta) + w * 64;
                        mbar_expect_tx(full, 16384);
                        tma_load(buf, &tmQ, 0, row, full);
                        tma_load(buf + 8192, &tmQ, 64, row, full);
                    } else if (t + 2 == NT) {
                        mbar_arrive(full);
                    }
                }
                asm volatile("cp.async.bulk.wait_group 0;" ::: "memory");
            }
        }
    } else {
        asm volatile("setmaxnreg.inc.sync.aligned.u32 240;");
        Consumer c;
        c.sb = sb; c.wg = warp >> 2; c.lane = lane; c.kph = 7; c.vph = 7;
        {
            const int row = (warp & 3) * 16 + (lane & 15);
            c.qaddr = sb + SM_Q + c.wg * 16384 + row * 128 + (((lane >> 4) ^ (row & 7)) << 4);
        }
        if (c.wg == 1) bar_arrive(1, 256);
        mbar_wait(bars + B_QFULL + 8 * c.wg, 0);
        c.load_q();
        fence_regs(c.Q);
        __syncwarp();
        if (lane == 0) mbar_arrive(bars + B_QREL + 8 * c.wg);
        c.wait_k(0, true);
        bar_sync(1 + c.wg, 256);
        wg_fence();
        c.issue_qk(0);
        bar_arrive(2 - c.wg, 256);
        wg_wait<0>();
        fence_regs(c.S);
        c.rel_k(0);
        c.l0 = c.l1 = 0.f;
        { float a0, a1; c.softmax<true>(a0, a1); }
        c.make_p();
        c.wait_k(1, true);
        c.wait_v(0, true);
        int base = 0;
#pragma unroll 1
        for (int t = 0; t < NT; t++) {
            const bool first = (FIRST_MASK >> t) & 1, last = (LAST_MASK >> t) & 1, more = t + 1 < NT;
            const int s0 = base, s1 = base == 2 ? 0 : base + 1, s2 = base == 0 ? 2 : base - 1;
            const int n0 = last ? s1 : s0, n1 = last ? s2 : s1;
            c.step<1>(s1, last, s0, true, s2, first, first, false, 0);
            c.step<2>(s2, last, s1, last, s0, true, first, false, 0);
            c.step<3>(s0, last, s2, last, n0, last && more, true, more, (t + 1) & 1);
            if (!more) break;
            c.step<0>(n0, true, s0, last, n1, last, last, false, 0);
            base = n0;
        }
        bar_sync(1 + c.wg, 256);
        wg_fence();
        c.issue_pv(base, 1);
        if (c.wg == 0) bar_arrive(2, 256);
        wg_wait<0>();
        fence_regs(c.O);
        mbar_wait(bars + B_QFULL + 8 * c.wg, NT & 1);
        c.epilogue(c.l0, c.l1);
        if (lane == 0) mbar_arrive(bars + B_DONE);
    }
}

typedef CUresult (*EncodeFn)(CUtensorMap*, CUtensorMapDataType, cuuint32_t, void*, const cuuint64_t*, const cuuint64_t*,
                             const cuuint32_t*, const cuuint32_t*, CUtensorMapInterleave, CUtensorMapSwizzle,
                             CUtensorMapL2promotion, CUtensorMapFloatOOBfill);

void make_map(EncodeFn enc, CUtensorMap* m, void* p, uint64_t rows, uint32_t box_rows) {
    cuuint64_t dims[2] = {128, rows};
    cuuint64_t strides[1] = {256};
    cuuint32_t box[2] = {64, box_rows};
    cuuint32_t es[2] = {1, 1};
    enc(m, CU_TENSOR_MAP_DATA_TYPE_BFLOAT16, 2, p, dims, strides, box, es, CU_TENSOR_MAP_INTERLEAVE_NONE,
        CU_TENSOR_MAP_SWIZZLE_128B, CU_TENSOR_MAP_L2_PROMOTION_L2_256B, CU_TENSOR_MAP_FLOAT_OOB_FILL_NONE);
}

}

extern "C" void kernel_launch(void* const* d_in, const int* in_sizes, int n_in, void* d_out, int out_size) {
    static EncodeFn enc = nullptr;
    if (!enc) {
        void* fn = nullptr;
        cudaDriverEntryPointQueryResult qr;
        cudaGetDriverEntryPoint("cuTensorMapEncodeTiled", &fn, cudaEnableDefault, &qr);
        enc = (EncodeFn)fn;
        cudaFuncSetAttribute(gqa_fwd_kernel, cudaFuncAttributeMaxDynamicSharedMemorySize, SM_TOTAL);
    }
    CUtensorMap tq, tk, tv, to;
    make_map(enc, &tq, d_in[0], 262144, 64);
    make_map(enc, &tk, d_in[1], 131072, 128);
    make_map(enc, &tv, d_in[2], 131072, 128);
    make_map(enc, &to, d_out, 262144, 64);
    gqa_fwd_kernel<<<NCTA, 384, SM_TOTAL>>>(tq, tk, tv, to);
}
```

```cpp
#include <cuda_runtime.h>
#include <cuda_bf16.h>
#include <cuda.h>
#include <stdint.h>

#define QR1 1
#define SCHED 4

namespace {

constexpr int NCTA = 128;
constexpr int NT   = 16;
constexpr int BLK_BYTES = 32768;

constexpr uint64_t PH_START_A = 0xEECCAA8866442210ull, PH_LOG_A = 0x1111111111111100ull, PH_START_B = 0xFDDBB99775533110ull, PH_LOG_B = 0x0111111111111110ull;
constexpr uint32_t mk_first(uint64_t st) { uint32_t m = 0; for (int i = 0; i < NT; i++) if ((int)((st >> (4 * i)) & 15) == i) m |= 1u << i; return m; }
constexpr uint32_t FIRST_A = mk_first(PH_START_A), FIRST_B = mk_first(PH_START_B);

constexpr uint32_t SM_K = 0;
constexpr uint32_t SM_V = 3 * BLK_BYTES;
constexpr uint32_t SM_Q = 6 * BLK_BYTES;
constexpr uint32_t SM_BAR = 7 * BLK_BYTES;
constexpr uint32_t SM_TOTAL = SM_BAR + 256 + 1024 + 512 + 1024;
constexpr uint32_t B_KFULL = 0, B_VFULL = 24, B_QFULL = 48, B_QREL = 64;

__device__ __forceinline__ uint32_t smem_u32(const void* p) { return (uint32_t)__cvta_generic_to_shared(p); }
__device__ __forceinline__ void mbar_init(uint32_t bar, uint32_t cnt) { asm volatile("mbarrier.init.shared::cta.b64 [%0], %1;" ::"r"(bar), "r"(cnt)); }
__device__ __forceinline__ void mbar_arrive(uint32_t bar) { asm volatile("mbarrier.arrive.shared::cta.b64 _, [%0];" ::"r"(bar) : "memory"); }
__device__ __forceinline__ void mbar_expect_tx(uint32_t bar, uint32_t bytes) { asm volatile("mbarrier.arrive.expect_tx.shared::cta.b64 _, [%0], %1;" ::"r"(bar), "r"(bytes) : "memory"); }
__device__ __forceinline__ bool mbar_try(uint32_t bar, uint32_t parity) {
    uint32_t ok;
    asm volatile("{.reg .pred p; mbarrier.try_wait.parity.shared::cta.b64 p, [%1], %2; selp.u32 %0,1,0,p;}" : "=r"(ok) : "r"(bar), "r"(parity) : "memory");
    return ok;
}
__device__ __forceinline__ void mbar_wait_b(uint32_t bar, uint32_t parity) {
#pragma unroll 1
    for (int i = 0; i < (1 << 22); i++) { if (mbar_try(bar, parity)) return; }
    __trap();
}
__device__ __forceinline__ void mbar_wait(uint32_t bar, uint32_t parity) {
    asm volatile("{\n.reg .pred p;\nLAB_WAIT:\nmbarrier.try_wait.parity.shared::cta.b64 p, [%0], %1;\n@!p bra LAB_WAIT;\n}" ::"r"(bar), "r"(parity) : "memory");
}
__device__ __forceinline__ void tma_load(uint32_t dst, const CUtensorMap* tm, int c0, int c1, uint32_t bar) {
    asm volatile("cp.async.bulk.tensor.2d.shared::cluster.global.mbarrier::complete_tx::bytes [%0], [%1, {%3, %4}], [%2];"
                 ::"r"(dst), "l"(tm), "r"(bar), "r"(c0), "r"(c1) : "memory");
}
__device__ __forceinline__ void tma_store(uint32_t src, const CUtensorMap* tm, int c0, int c1) {
    asm volatile("cp.async.bulk.tensor.2d.global.shared::cta.bulk_group [%1, {%2, %3}], [%0];"
                 ::"r"(src), "l"(tm), "r"(c0), "r"(c1) : "memory");
}
constexpr uint64_t POL_FIRST = 0x12F0000000000000ull, POL_NORMAL = 0x1000000000000000ull;
__device__ __forceinline__ void tma_load_h(uint32_t dst, const CUtensorMap* tm, int c0, int c1, uint32_t bar, uint64_t pol) {
    asm volatile("cp.async.bulk.tensor.2d.shared::cluster.global.mbarrier::complete_tx::bytes.L2::cache_hint [%0], [%1, {%3, %4}], [%2], %5;"
                 ::"r"(dst), "l"(tm), "r"(bar), "r"(c0), "r"(c1), "l"(pol) : "memory");
}
__device__ __forceinline__ void tma_store_h(uint32_t src, const CUtensorMap* tm, int c0, int c1, uint64_t pol) {
    asm volatile("cp.async.bulk.tensor.2d.global.shared::cta.bulk_group.L2::cache_hint [%1, {%2, %3}], [%0], %4;"
                 ::"r"(src), "l"(tm), "r"(c0), "r"(c1), "l"(pol) : "memory");
}
#define EF_Q 1
#define EF_O 1
#define EF_KV 0
__device__ __forceinline__ void l2_prefetch(const void* p, uint32_t bytes) {
    asm volatile("cp.async.bulk.prefetch.L2.global [%0], %1;" ::"l"(p), "r"(bytes) : "memory");
}
__device__ __forceinline__ void bar_sync(int id, int n) { asm volatile("bar.sync %0, %1;" ::"r"(id), "r"(n) : "memory"); }
__device__ __forceinline__ void bar_arrive(int id, int n) { asm volatile("bar.arrive %0, %1;" ::"r"(id), "r"(n) : "memory"); }
__device__ __forceinline__ void wg_fence() { asm volatile("wgmma.fence.sync.aligned;" ::: "memory"); }
__device__ __forceinline__ void wg_commit() { asm volatile("wgmma.commit_group.sync.aligned;" ::: "memory"); }
template <int N> __device__ __forceinline__ void wg_wait() { asm volatile("wgmma.wait_group.sync.aligned %0;" ::"n"(N) : "memory"); }

__device__ __forceinline__ uint64_t mkdesc(uint32_t addr, uint32_t lbo, uint32_t sbo) {
    uint64_t d = 0;
    d |= (uint64_t)((addr & 0x3FFFF) >> 4);
    d |= (uint64_t)((lbo & 0x3FFFF) >> 4) << 16;
    d |= (uint64_t)((sbo & 0x3FFFF) >> 4) << 32;
    d |= (uint64_t)1 << 62;
    return d;
}

#define R8(d, o) "+f"(d[o + 0]), "+f"(d[o + 1]), "+f"(d[o + 2]), "+f"(d[o + 3]), "+f"(d[o + 4]), "+f"(d[o + 5]), "+f"(d[o + 6]), "+f"(d[o + 7])
#define R64(d) R8(d, 0), R8(d, 8), R8(d, 16), R8(d, 24), R8(d, 32), R8(d, 40), R8(d, 48), R8(d, 56)
#define D64 "{%0,%1,%2,%3,%4,%5,%6,%7,%8,%9,%10,%11,%12,%13,%14,%15,%16,%17,%18,%19,%20,%21,%22,%23,%24,%25,%26,%27,%28,%29,%30,%31,%32,%33,%34,%35,%36,%37,%38,%39,%40,%41,%42,%43,%44,%45,%46,%47,%48,%49,%50,%51,%52,%53,%54,%55,%56,%57,%58,%59,%60,%61,%62,%63}"

template <int TB>
__device__ __forceinline__ void wgmma_rs(float (&d)[64], uint32_t a0, uint32_t a1, uint32_t a2, uint32_t a3, uint64_t db, int scale_d) {
    asm volatile("{.reg .pred p; setp.ne.b32 p, %69, 0;\n"
                 "wgmma.mma_async.sync.aligned.m64n128k16.f32.bf16.bf16 " D64 ", {%64,%65,%66,%67}, %68, p, 1, 1, %70;}\n"
                 : R64(d) : "r"(a0), "r"(a1), "r"(a2), "r"(a3), "l"(db), "r"(scale_d), "n"(TB));
}
__device__ __forceinline__ void fence_regs(float (&d)[64]) { asm volatile("" : R64(d)::"memory"); }
__device__ __forceinline__ void fence_regs(uint32_t (&d)[32]) {
#pragma unroll
    for (int i = 0; i < 32; i++) asm volatile("" : "+r"(d[i])::"memory");
}
__device__ __forceinline__ float ex2(float x) { float y; asm("ex2.approx.ftz.f32 %0, %1;" : "=f"(y) : "f"(x)); return y; }
__device__ __forceinline__ uint32_t pack_bf16(float lo, float hi) { uint32_t r; asm("cvt.rn.bf16x2.f32 %0, %1, %2;" : "=r"(r) : "f"(hi), "f"(lo)); return r; }
__device__ __forceinline__ void ldsm4(uint32_t addr, uint32_t& a, uint32_t& b, uint32_t& c, uint32_t& d) {
    asm volatile("ldmatrix.sync.aligned.m8n8.x4.shared.b16 {%0,%1,%2,%3}, [%4];" : "=r"(a), "=r"(b), "=r"(c), "=r"(d) : "r"(addr) : "memory");
}
__device__ __forceinline__ void ldsm4_if(int p, uint32_t addr, uint32_t& a, uint32_t& b, uint32_t& c, uint32_t& d) {
    asm volatile("{.reg .pred p; setp.ne.b32 p, %5, 0; @p ldmatrix.sync.aligned.m8n8.x4.shared.b16 {%0,%1,%2,%3}, [%4];}" : "+r"(a), "+r"(b), "+r"(c), "+r"(d) : "r"(addr), "r"(p) : "memory");
}
__device__ __forceinline__ void stsm4(uint32_t addr, uint32_t a, uint32_t b, uint32_t c, uint32_t d) {
    asm volatile("stmatrix.sync.aligned.m8n8.x4.shared.b16 [%4], {%0,%1,%2,%3};" ::"r"(a), "r"(b), "r"(c), "r"(d), "r"(addr) : "memory");
}

__device__ __forceinline__ int tile_qrow(int t, int cta) {
    const bool g = cta >= 64;
    const int c = cta & 63;
    const int st = ((g ? PH_START_B : PH_START_A) >> (4 * t)) & 15, lg = ((g ? PH_LOG_B : PH_LOG_A) >> (4 * t)) & 15;
    const int head = (g ? 128 : 0) + 8 * st + (c >> (3 - lg));
    const int qt = ((c & ((8 >> lg) - 1)) << lg) + (t - st);
    return head * 1024 + qt * 128;
}
#define PF_C0 6
#define PF_C1 10
#define PF_CL 16
struct PfOrder { uint8_t o[2][128]; };
constexpr PfOrder mk_order() {
    PfOrder r{};
    for (int g = 0; g < 2; g++) {
        int c = 0;
        for (int d = -8; d < 140; d++)
            for (int p = 0; p < 128; p++) {
                const int v = p & 63, t = v >> 2;
                const int st = ((g ? PH_START_B : PH_START_A) >> (4 * t)) & 15, lg = ((g ? PH_LOG_B : PH_LOG_A) >> (4 * t)) & 15;
                const int b = ((v - 4 * st) << (3 - lg)) >> 2;
                const int dl = p < 64 ? 8 * t - 6 + ((v >> 1) & 1) : 2 * (4 * st + (b >> 1) - 2 + (b & 1)) + 1;
                if (dl == d) r.o[g][c++] = p;
            }
    }
    return r;
}
__constant__ PfOrder PF_ORDER = mk_order();
__device__ __forceinline__ void ld_pf(uint32_t dummy, const char* p) {
    asm volatile("cp.async.cg.shared.global.L2::256B [%0], [%1], 16;" ::"r"(dummy), "l"(p) : "memory");
}
__device__ __forceinline__ const char* kv_piece(int v, int cta, const char* k, const char* vv) {
    const bool g = cta >= 64;
    const int c = cta & 63, t = v >> 2;
    const int st = ((g ? PH_START_B : PH_START_A) >> (4 * t)) & 15, lg = ((g ? PH_LOG_B : PH_LOG_A) >> (4 * t)) & 15;
    const int head = (g ? 128 : 0) + 8 * st + (c >> (3 - lg));
    const int x = ((v - 4 * st) << (3 - lg)) + (c & ((8 >> lg) - 1));
    return ((x & 4) ? vv : k) + (size_t)(head * 16 + (x >> 3) * 4 + (x & 3)) * 8192;
}
__device__ __forceinline__ void mma16816(float& c0, float& c1, float& c2, float& c3, uint32_t a0, uint32_t a1, uint32_t a2, uint32_t a3, uint32_t b0, uint32_t b1) {
    asm volatile("mma.sync.aligned.m16n8k16.row.col.f32.bf16.bf16.f32 {%0,%1,%2,%3}, {%4,%5,%6,%7}, {%8,%9}, {%0,%1,%2,%3};"
                 : "+f"(c0), "+f"(c1), "+f"(c2), "+f"(c3) : "r"(a0), "r"(a1), "r"(a2), "r"(a3), "r"(b0), "r"(b1));
}
__device__ __forceinline__ float rcp(float x) { float y; asm("rcp.approx.ftz.f32 %0, %1;" : "=f"(y) : "f"(x)); return y; }

constexpr float SCALE_LOG2 = 0.08838834764831845f * 1.4426950408889634f;

#define TS(w, n, i)
#define GT(i)

constexpr float L_LO = 5.9604644775390625e-8f;
constexpr float L_HI = 1099511627776.f;
#define LDQ 2
#define EPI 0
#define NB 11
#define NSPLIT 8

struct Consumer {
    float S[64], O[64];
    uint32_t P[32], Q[32];
    float m0, m1, l0, l1;
    uint32_t sb, qaddr;
    int wg, lane;

    __device__ __forceinline__ void load_q() {
#pragma unroll
        for (int s = 0; s < 8; s++) ldsm4((qaddr ^ ((s & 3) << 5)) + (s >> 2) * 8192, Q[4 * s], Q[4 * s + 1], Q[4 * s + 2], Q[4 * s + 3]);
    }
    __device__ __forceinline__ void load_q_if(int p) {
#pragma unroll
        for (int s = 0; s < 8; s++) ldsm4_if(p, (qaddr ^ ((s & 3) << 5)) + (s >> 2) * 8192, Q[4 * s], Q[4 * s + 1], Q[4 * s + 2], Q[4 * s + 3]);
    }
    __device__ __forceinline__ void issue_qk(int slot) {
        uint64_t dk = mkdesc(sb + SM_K + slot * BLK_BYTES, 16, 1024);
#pragma unroll
        for (int k = 0; k < 8; k++) wgmma_rs<0>(S, Q[4 * k], Q[4 * k + 1], Q[4 * k + 2], Q[4 * k + 3], dk + ((k >> 2) * 1024 + (k & 3) * 2), k != 0);
    }
    __device__ __forceinline__ void issue_pv(int slot, int acc) {
        uint64_t dv = mkdesc(sb + SM_V + slot * BLK_BYTES, 16384, 1024);
#pragma unroll
        for (int k = 0; k < 8; k++) wgmma_rs<1>(O, P[4 * k], P[4 * k + 1], P[4 * k + 2], P[4 * k + 3], dv + k * 128, k != 0 || acc);
    }
    template <int B, int E>
    __device__ __forceinline__ void exp_sum(float& u0, float& u1) {
#pragma unroll
        for (int i = B; i < E; i++) {
            S[4 * i]     = ex2(fmaf(S[4 * i],     SCALE_LOG2, -m0));
            S[4 * i + 1] = ex2(fmaf(S[4 * i + 1], SCALE_LOG2, -m0));
            S[4 * i + 2] = ex2(fmaf(S[4 * i + 2], SCALE_LOG2, -m1));
            S[4 * i + 3] = ex2(fmaf(S[4 * i + 3], SCALE_LOG2, -m1));
            l0 += S[4 * i]; u0 = i ? u0 + S[4 * i + 1] : S[4 * i + 1];
            l1 += S[4 * i + 2]; u1 = i ? u1 + S[4 * i + 3] : S[4 * i + 3];
        }
        if (E == 16) { l0 += u0; l1 += u1; }
    }
    __device__ __forceinline__ void redo_block(const char* gq, int t, int slot, float lo0, float lo1, bool fresh) {
        const uint32_t* qp = (const uint32_t*)(gq + (size_t)(tile_qrow(t, blockIdx.x) + (threadIdx.x >> 5) * 16 + (lane >> 2)) * 256) + (lane & 3);
#pragma unroll
        for (int s = 0; s < 8; s++) { Q[4 * s] = qp[8 * s]; Q[4 * s + 1] = qp[8 * s + 512]; Q[4 * s + 2] = qp[8 * s + 4]; Q[4 * s + 3] = qp[8 * s + 516]; }
        uint32_t kb = sb + SM_K + slot * BLK_BYTES + (lane & 7) * 128 + (((lane >> 3) ^ (lane & 7)) << 4);
#pragma unroll
        for (int n = 0; n < 16; n++) {
            if (n) kb += __float_as_uint(S[4 * n - 1]) & blockIdx.y;
            S[4 * n] = S[4 * n + 1] = S[4 * n + 2] = S[4 * n + 3] = 0.f;
#pragma unroll
            for (int k = 0; k < 4; k++) {
                uint32_t b0, b1, b2, b3;
                ldsm4((kb ^ ((k & 1) << 6)) + n * 1024 + (k >> 1) * 16384, b0, b1, b2, b3);
                mma16816(S[4 * n], S[4 * n + 1], S[4 * n + 2], S[4 * n + 3], Q[8 * k], Q[8 * k + 1], Q[8 * k + 2], Q[8 * k + 3], b0, b1);
                mma16816(S[4 * n], S[4 * n + 1], S[4 * n + 2], S[4 * n + 3], Q[8 * k + 4], Q[8 * k + 5], Q[8 * k + 6], Q[8 * k + 7], b2, b3);
            }
        }
        float x0 = fmaxf(S[0], S[1]), x1 = fmaxf(S[2], S[3]);
#pragma unroll
        for (int i = 1; i < 16; i++) {
            x0 = fmaxf(x0, fmaxf(S[4 * i], S[4 * i + 1]));
            x1 = fmaxf(x1, fmaxf(S[4 * i + 2], S[4 * i + 3]));
        }
        x0 = fmaxf(x0, __shfl_xor_sync(0xffffffffu, x0, 1));
        x1 = fmaxf(x1, __shfl_xor_sync(0xffffffffu, x1, 1));
        x0 = fmaxf(x0, __shfl_xor_sync(0xffffffffu, x0, 2));
        x1 = fmaxf(x1, __shfl_xor_sync(0xffffffffu, x1, 2));
        x0 *= SCALE_LOG2; x1 *= SCALE_LOG2;
        if (!fresh) {
            x0 = fmaxf(x0, m0); x1 = fmaxf(x1, m1);
            const float a0 = ex2(m0 - x0), a1 = ex2(m1 - x1);
            lo0 *= a0; lo1 *= a1;
#pragma unroll
            for (int i = 0; i < 16; i++) { O[4 * i] *= a0; O[4 * i + 1] *= a0; O[4 * i + 2] *= a1; O[4 * i + 3] *= a1; }
        }
        m0 = x0; m1 = x1;
        l0 = lo0; l1 = lo1;
        float u0, u1;
        exp_sum<0, 16>(u0, u1);
        make_p();
    }
    __device__ __forceinline__ void make_p() {
#pragma unroll
        for (int i = 0; i < 32; i++) P[i] = pack_bf16(S[2 * i], S[2 * i + 1]);
    }
    __device__ __forceinline__ void row_rcp(float& r0, float& r1) {
        float e0 = l0 + __shfl_xor_sync(0xffffffffu, l0, 1), e1 = l1 + __shfl_xor_sync(0xffffffffu, l1, 1);
        e0 += __shfl_xor_sync(0xffffffffu, e0, 2); e1 += __shfl_xor_sync(0xffffffffu, e1, 2);
        r0 = rcp(e0); r1 = rcp(e1);
    }
    __device__ __forceinline__ void epilogue(float r0, float r1, uint32_t (&E)[32]) {
#pragma unroll
        for (int s = 0; s < 8; s++) {
            E[4 * s] = pack_bf16(O[8 * s] * r0, O[8 * s + 1] * r0); E[4 * s + 1] = pack_bf16(O[8 * s + 2] * r1, O[8 * s + 3] * r1);
            E[4 * s + 2] = pack_bf16(O[8 * s + 4] * r0, O[8 * s + 5] * r0); E[4 * s + 3] = pack_bf16(O[8 * s + 6] * r1, O[8 * s + 7] * r1);
            stsm4((qaddr ^ ((s & 3) << 5)) + (s >> 2) * 8192, E[4 * s], E[4 * s + 1], E[4 * s + 2], E[4 * s + 3]);
        }
    }

    __device__ __forceinline__ void run(uint32_t first, const char* gq) {
        int ks = 0;
        float r0, r1;
        uint32_t zero = blockIdx.y;
        asm volatile("" : "+r"(zero));
        m0 = m1 = l0 = l1 = 0.f;
        bar_sync(1 + wg, 288);
        wg_fence();
        issue_qk(0);
        wg_commit();
        bar_arrive(2 - wg, 288);
        wg_wait<0>();
#pragma unroll 1
        for (int i = 0;; i++) {
            const int j = i & 3;
            fence_regs(S);
            row_rcp(r0, r1);
            if (j == 0) l0 = l1 = 0.f;
            const float lo0 = l0, lo1 = l1;
            float u0, u1;
            exp_sum<0, NSPLIT>(u0, u1);
            if (l0 + u0 + l1 + u1 < 0.f) __trap();
            wg_wait<0>();
            fence_regs(O);
            fence_regs(P);
            if (j == 0 && i > 0) {
                uint32_t E[32];
                epilogue(r0, r1, E);
                exp_sum<NSPLIT, 16>(u0, u1);
                make_p();
            } else if (j == 3) {
                uint32_t tm;
#pragma unroll
                for (int s = 0; s < 8; s++) {
                    if (s == 7) asm volatile("mov.u32 %0, %%clock;" : "=r"(tm)::"memory");
                    ldsm4((qaddr ^ ((s & 3) << 5)) + (s >> 2) * 8192, Q[4 * s], Q[4 * s + 1], Q[4 * s + 2], Q[4 * s + 3]);
                }
                fence_regs(S);
                exp_sum<NSPLIT, 16>(u0, u1);
                make_p();
                uint32_t z = __float_as_uint(l0) & __float_as_uint(l1) & tm;
                l0 = __uint_as_float(__float_as_uint(l0) | (z & Q[31] & zero));
            } else {
                exp_sum<NSPLIT, 16>(u0, u1);
                make_p();
            }
            const bool redo = __any_sync(0xffffffffu, !(l0 + l1 <= L_HI && fminf(l0, l1) >= L_LO));
            if (__builtin_expect(redo, 0)) { redo_block(gq, i >> 2, ks, lo0, lo1, j == 0); load_q_if(j == 3); }
            const int vs = ks;
            if (j != 3 || ((first >> ((i + 1) >> 2)) & 1)) ks = ks == 2 ? 0 : ks + 1;
            if (i == 4 * NT - 1) break;
            bar_sync(1 + wg, 288);
            wg_fence();
            issue_qk(ks);
            wg_commit();
            issue_pv(vs, j != 0);
            wg_commit();
            bar_arrive(2 - wg, 288);
            wg_wait<1>();
        }
        bar_sync(1 + wg, 288);
        wg_fence();
        issue_pv(ks, 1);
        wg_commit();
        if (wg == 0) bar_arrive(2, 288);
        row_rcp(r0, r1);
        wg_wait<0>();
        fence_regs(O);
        epilogue(r0, r1, P);
        bar_arrive(3 + wg, 160);
    }
};

__global__ void __launch_bounds__(384, 1)
gqa_fwd_kernel(const __grid_constant__ CUtensorMap tmQ, const __grid_constant__ CUtensorMap tmK,
               const __grid_constant__ CUtensorMap tmV, const __grid_constant__ CUtensorMap tmO,
               const char* __restrict__ gq, const char* __restrict__ gk, const char* __restrict__ gv) {
    extern __shared__ char smem_raw[];
    const uint32_t sb = (smem_u32(smem_raw) + 1023) & ~1023u;
    const uint32_t bars = sb + SM_BAR;
    const int warp = __shfl_sync(0xffffffffu, threadIdx.x >> 5, 0);
    const int lane = threadIdx.x & 31;
    const int cta = blockIdx.x;
    const uint32_t first = cta >= 64 ? FIRST_B : FIRST_A;

    if (threadIdx.x == 0) {
        for (int i = 0; i < 12; i++) mbar_init(bars + 8 * i, 1);
        asm volatile("fence.mbarrier_init.release.cluster;" ::: "memory");
    }
    __syncthreads();

    if (warp >= 8) {
        asm volatile("setmaxnreg.dec.sync.aligned.u32 24;");
        if (warp == 8) {
            uint32_t kph = 0, vph = 0;
            int slot = 0, pslot = 0;
            bool pfresh = false;
            TS(0, 66, 0); GT(0);
            const char** pft = (const char**)(smem_raw + (bars + 256 - smem_u32(smem_raw)));
#pragma unroll 1
            for (int k = lane; k < 128; k += 32) {
                const int p = PF_ORDER.o[cta >= 64][k];
                pft[k] = p < 64 ? gq + (size_t)(tile_qrow(p >> 2, cta) / 32 + (p & 3)) * 8192 : kv_piece(p - 64, cta, gk, gv);
            }
            __syncwarp();
            const uint32_t pfd = bars + 256 + 1024 + lane * 16;
            int pc = PF_C1;
#pragma unroll
            for (int k = PF_C0; k < PF_C1; k++) ld_pf(pfd, pft[k] + lane * 256);
#pragma unroll 1
            for (int n = 0; n <= 4 * NT; n++) {
                const bool fresh = (n & 3) == 3 || ((first >> (n >> 2)) & 1);
                if (fresh) { mbar_wait_b(bars + B_KFULL + 8 * slot, (kph >> slot) & 1); kph ^= 1u << slot; }
                TS(0, n, 2);
                if (pfresh) { mbar_wait_b(bars + B_VFULL + 8 * pslot, (vph >> pslot) & 1); vph ^= 1u << pslot; }
                TS(0, n, 3);
                if ((n & 3) == 3) mbar_wait_b(bars + B_QFULL, ((n >> 2) + 1) & 1);
                TS(0, n, 0);
                bar_sync(1, 288);
                TS(0, n, 1);
                if ((n & 3) == 1 && lane == 0) mbar_arrive(bars + B_QREL);
                {
                    const int e = min(min(PF_C1 + 3 * n + 3, PF_CL + 2 * n + 2), 128);
                    if (pc < e) ld_pf(pfd, pft[pc] + lane * 256);
                    if (pc + 1 < e) ld_pf(pfd, pft[pc + 1] + lane * 256);
                    if (pc + 2 < e) ld_pf(pfd, pft[pc + 2] + lane * 256);
                    pc = e;
                }
                pslot = slot; pfresh = fresh;
                if ((n & 3) != 3 || ((first >> ((n + 1) >> 2)) & 1)) slot = slot == 2 ? 0 : slot + 1;
            }
            asm volatile("cp.async.wait_all;" ::: "memory");
            bar_sync(3, 160);
            TS(0, 65, 1);
            if (lane == 0) mbar_arrive(bars + B_QREL);
        } else if (warp == 9) {
            int slot = 0, pslot = 0, prow = -1, flip = 0;
            bool plast = false;
#pragma unroll 1
            for (int n = -2; n <= 4 * NT; n++) {
                if (n >= 0) {
                    if ((n & 3) == 3) mbar_wait_b(bars + B_QFULL + 8, ((n >> 2) + 1) & 1);
                    TS(1, n, 0);
                    bar_sync(2, 288);
                    TS(1, n, 1);
                }
                const int a = n + 2, j = a & 3;
                const bool fst = (first >> (a >> 2)) & 1;
                if (j == 0) flip = fst ? 0 : flip ^ 1;
                int row = -1;
                if (a < 4 * NT && (fst || j == 3)) row = (tile_qrow(a >> 2, cta) >> 10) * 512 + (flip ? 0 : j) * 128;
                const uint32_t nx = (first | 0x30000u) >> ((a >> 2) + 1);
                const bool last = EF_KV && (j == 1 || j == 2 || (nx & (j == 0 ? 1 : 3)));
                if (lane == 0) {
                    if (row >= 0) {
                        const uint32_t full = bars + B_KFULL + 8 * slot, buf = sb + SM_K + slot * BLK_BYTES;
                        mbar_expect_tx(full, BLK_BYTES);
                        tma_load_h(buf, &tmK, 0, row, full, last ? POL_FIRST : POL_NORMAL);
                        tma_load_h(buf + 16384, &tmK, 64, row, full, last ? POL_FIRST : POL_NORMAL);
                    }
                    if (prow >= 0) {
                        const uint32_t full = bars + B_VFULL + 8 * pslot, buf = sb + SM_V + pslot * BLK_BYTES;
                        mbar_expect_tx(full, BLK_BYTES);
                        tma_load_h(buf, &tmV, 0, prow, full, plast ? POL_FIRST : POL_NORMAL);
                        tma_load_h(buf + 16384, &tmV, 64, prow, full, plast ? POL_FIRST : POL_NORMAL);
                    }
                }
                if (n >= 0 && (n & 3) == 1 && lane == 0) mbar_arrive(bars + B_QREL + 8);
                __syncwarp();
                pslot = slot; prow = row; plast = last;
                if (j != 3 || ((first >> ((a + 1) >> 2)) & 1)) slot = slot == 2 ? 0 : slot + 1;
            }
            bar_sync(4, 160);
            TS(1, 65, 1);
            if (lane == 0) mbar_arrive(bars + B_QREL + 8);
        } else if (lane == 0) {
            const int w = warp - 10;
            const uint32_t buf = sb + SM_Q + w * 16384;
            const uint32_t full = bars + B_QFULL + 8 * w, rel = bars + B_QREL + 8 * w;
#pragma unroll 1
            for (int t = -2; t < NT; t++) {
                if (t >= -1) mbar_wait_b(rel, (t + 1) & 1);
                if (t >= -1) TS(w, 4 * t + 5, 4);
                if (t >= 0) {
                    const int row = tile_qrow(t, cta) + w * 64;
                    asm volatile("fence.proxy.async.shared::cta;" ::: "memory");
                    tma_store_h(buf, &tmO, 0, row, EF_O ? POL_FIRST : POL_NORMAL);
                    tma_store_h(buf + 8192, &tmO, 64, row, EF_O ? POL_FIRST : POL_NORMAL);
                    asm volatile("cp.async.bulk.commit_group;" ::: "memory");
                    asm volatile("cp.async.bulk.wait_group.read 0;" ::: "memory");
                }
                if (t >= -1) TS(w, 4 * t + 5, 5);
                if (t + 2 < NT) {
                    const int row = tile_qrow(t + 2, cta) + w * 64;
                    mbar_expect_tx(full, 16384);
                    tma_load_h(buf, &tmQ, 0, row, full, EF_Q ? POL_FIRST : POL_NORMAL);
                    tma_load_h(buf + 8192, &tmQ, 64, row, full, EF_Q ? POL_FIRST : POL_NORMAL);
                } else if (t + 2 == NT) {
                    mbar_arrive(full);
                }
            }
            asm volatile("cp.async.bulk.wait_group 0;" ::: "memory");
            if (w == 1) { TS(1, 66, 1); GT(1); }
        }
    } else {
        asm volatile("setmaxnreg.inc.sync.aligned.u32 240;");
        Consumer c;
        c.sb = sb; c.wg = warp >> 2; c.lane = lane;
        {
            const int row = (warp & 3) * 16 + (lane & 15);
            c.qaddr = sb + SM_Q + c.wg * 16384 + row * 128 + (((lane >> 4) ^ (row & 7)) << 4);
        }
        if (c.wg == 1) bar_arrive(1, 288);
        mbar_wait(bars + B_QFULL + 8 * c.wg, 0);
        c.load_q();
        c.run(first, gq);
    }
}

typedef CUresult (*EncodeFn)(CUtensorMap*, CUtensorMapDataType, cuuint32_t, void*, const cuuint64_t*, const cuuint64_t*,
                             const cuuint32_t*, const cuuint32_t*, CUtensorMapInterleave, CUtensorMapSwizzle,
                             CUtensorMapL2promotion, CUtensorMapFloatOOBfill);

void make_map(EncodeFn enc, CUtensorMap* m, void* p, uint64_t rows, uint32_t box_rows) {
    cuuint64_t dims[2] = {128, rows};
    cuuint64_t strides[1] = {256};
    cuuint32_t box[2] = {64, box_rows};
    cuuint32_t es[2] = {1, 1};
    enc(m, CU_TENSOR_MAP_DATA_TYPE_BFLOAT16, 2, p, dims, strides, box, es, CU_TENSOR_MAP_INTERLEAVE_NONE,
        CU_TENSOR_MAP_SWIZZLE_128B, CU_TENSOR_MAP_L2_PROMOTION_L2_256B, CU_TENSOR_MAP_FLOAT_OOB_FILL_NONE);
}

}

extern "C" void kernel_launch(void* const* d_in, const int* in_sizes, int n_in, void* d_out, int out_size) {
    static EncodeFn enc = nullptr;
    if (!enc) {
        void* fn = nullptr;
        cudaDriverEntryPointQueryResult qr;
        cudaGetDriverEntryPoint("cuTensorMapEncodeTiled", &fn, cudaEnableDefault, &qr);
        enc = (EncodeFn)fn;
        cudaFuncSetAttribute(gqa_fwd_kernel, cudaFuncAttributeMaxDynamicSharedMemorySize, SM_TOTAL);
    }
    CUtensorMap tq, tk, tv, to;
    make_map(enc, &tq, d_in[0], 262144, 64);
    make_map(enc, &tk, d_in[1], 131072, 128);
    make_map(enc, &tv, d_in[2], 131072, 128);
    make_map(enc, &to, d_out, 262144, 64);
    gqa_fwd_kernel<<<NCTA, 384, SM_TOTAL>>>(tq, tk, tv, to, (const char*)d_in[0], (const char*)d_in[1], (const char*)d_in[2]);
}
```

```cpp
#include <cuda_runtime.h>
#include <cuda_bf16.h>
#include <cuda.h>
#include <stdint.h>

#define SCHED 4
#define PFG 1

namespace {

constexpr int NCTA = 128;
constexpr int NT   = 16;
constexpr int BLK_BYTES = 32768;

constexpr uint64_t PH_START_A = 0xEECCAA8866442210ull, PH_LOG_A = 0x1111111111111100ull, PH_START_B = 0xFDDBB99775533110ull, PH_LOG_B = 0x0111111111111110ull;
constexpr uint32_t mk_first(uint64_t st) { uint32_t m = 0; for (int i = 0; i < NT; i++) if ((int)((st >> (4 * i)) & 15) == i) m |= 1u << i; return m; }
constexpr uint32_t FIRST_A = mk_first(PH_START_A), FIRST_B = mk_first(PH_START_B);

constexpr uint32_t SM_K = 0;
constexpr uint32_t SM_V = 3 * BLK_BYTES;
constexpr uint32_t SM_Q = 6 * BLK_BYTES;
constexpr uint32_t SM_BAR = 7 * BLK_BYTES;
constexpr uint32_t SM_TOTAL = SM_BAR + 256 + 1024 + 512 + 1024;
constexpr uint32_t B_KFULL = 0, B_VFULL = 24, B_QFULL = 48, B_QREL = 56;

__device__ __forceinline__ uint32_t smem_u32(const void* p) { return (uint32_t)__cvta_generic_to_shared(p); }
__device__ __forceinline__ void mbar_init(uint32_t bar, uint32_t cnt) { asm volatile("mbarrier.init.shared::cta.b64 [%0], %1;" ::"r"(bar), "r"(cnt)); }
__device__ __forceinline__ void mbar_arrive(uint32_t bar) { asm volatile("mbarrier.arrive.shared::cta.b64 _, [%0];" ::"r"(bar) : "memory"); }
__device__ __forceinline__ void mbar_expect_tx(uint32_t bar, uint32_t bytes) { asm volatile("mbarrier.arrive.expect_tx.shared::cta.b64 _, [%0], %1;" ::"r"(bar), "r"(bytes) : "memory"); }
__device__ __forceinline__ bool mbar_try(uint32_t bar, uint32_t parity) {
    uint32_t ok;
    asm volatile("{.reg .pred p; mbarrier.try_wait.parity.shared::cta.b64 p, [%1], %2; selp.u32 %0,1,0,p;}" : "=r"(ok) : "r"(bar), "r"(parity) : "memory");
    return ok;
}
__device__ __forceinline__ void mbar_wait_b(uint32_t bar, uint32_t parity) {
#pragma unroll 1
    for (int i = 0; i < (1 << 22); i++) { if (mbar_try(bar, parity)) return; }
    __trap();
}
__device__ __forceinline__ void mbar_wait(uint32_t bar, uint32_t parity) {
    asm volatile("{\n.reg .pred p;\nLAB_WAIT:\nmbarrier.try_wait.parity.shared::cta.b64 p, [%0], %1;\n@!p bra LAB_WAIT;\n}" ::"r"(bar), "r"(parity) : "memory");
}
__device__ __forceinline__ void tma_load(uint32_t dst, const CUtensorMap* tm, int c0, int c1, uint32_t bar) {
    asm volatile("cp.async.bulk.tensor.2d.shared::cluster.global.mbarrier::complete_tx::bytes [%0], [%1, {%3, %4}], [%2];"
                 ::"r"(dst), "l"(tm), "r"(bar), "r"(c0), "r"(c1) : "memory");
}
__device__ __forceinline__ void tma_store(uint32_t src, const CUtensorMap* tm, int c0, int c1) {
    asm volatile("cp.async.bulk.tensor.2d.global.shared::cta.bulk_group [%1, {%2, %3}], [%0];"
                 ::"r"(src), "l"(tm), "r"(c0), "r"(c1) : "memory");
}
constexpr uint64_t POL_FIRST = 0x12F0000000000000ull, POL_NORMAL = 0x1000000000000000ull;
__device__ __forceinline__ void tma_load_h(uint32_t dst, const CUtensorMap* tm, int c0, int c1, uint32_t bar, uint64_t pol) {
    asm volatile("cp.async.bulk.tensor.2d.shared::cluster.global.mbarrier::complete_tx::bytes.L2::cache_hint [%0], [%1, {%3, %4}], [%2], %5;"
                 ::"r"(dst), "l"(tm), "r"(bar), "r"(c0), "r"(c1), "l"(pol) : "memory");
}
__device__ __forceinline__ void tma_store_h(uint32_t src, const CUtensorMap* tm, int c0, int c1, uint64_t pol) {
    asm volatile("cp.async.bulk.tensor.2d.global.shared::cta.bulk_group.L2::cache_hint [%1, {%2, %3}], [%0], %4;"
                 ::"r"(src), "l"(tm), "r"(c0), "r"(c1), "l"(pol) : "memory");
}
#define EF_Q 1
#define EF_O 1
#define EF_KV 0
__device__ __forceinline__ void l2_prefetch(const void* p, uint32_t bytes) {
    asm volatile("cp.async.bulk.prefetch.L2.global [%0], %1;" ::"l"(p), "r"(bytes) : "memory");
}
__device__ __forceinline__ void bar_sync(int id, int n) { asm volatile("bar.sync %0, %1;" ::"r"(id), "r"(n) : "memory"); }
__device__ __forceinline__ void bar_arrive(int id, int n) { asm volatile("bar.arrive %0, %1;" ::"r"(id), "r"(n) : "memory"); }
__device__ __forceinline__ void wg_fence() { asm volatile("wgmma.fence.sync.aligned;" ::: "memory"); }
__device__ __forceinline__ void wg_commit() { asm volatile("wgmma.commit_group.sync.aligned;" ::: "memory"); }
template <int N> __device__ __forceinline__ void wg_wait() { asm volatile("wgmma.wait_group.sync.aligned %0;" ::"n"(N) : "memory"); }

__device__ __forceinline__ uint64_t mkdesc(uint32_t addr, uint32_t lbo, uint32_t sbo) {
    uint64_t d = 0;
    d |= (uint64_t)((addr & 0x3FFFF) >> 4);
    d |= (uint64_t)((lbo & 0x3FFFF) >> 4) << 16;
    d |= (uint64_t)((sbo & 0x3FFFF) >> 4) << 32;
    d |= (uint64_t)1 << 62;
    return d;
}

#define R8(d, o) "+f"(d[o + 0]), "+f"(d[o + 1]), "+f"(d[o + 2]), "+f"(d[o + 3]), "+f"(d[o + 4]), "+f"(d[o + 5]), "+f"(d[o + 6]), "+f"(d[o + 7])
#define R64(d) R8(d, 0), R8(d, 8), R8(d, 16), R8(d, 24), R8(d, 32), R8(d, 40), R8(d, 48), R8(d, 56)
#define D64 "{%0,%1,%2,%3,%4,%5,%6,%7,%8,%9,%10,%11,%12,%13,%14,%15,%16,%17,%18,%19,%20,%21,%22,%23,%24,%25,%26,%27,%28,%29,%30,%31,%32,%33,%34,%35,%36,%37,%38,%39,%40,%41,%42,%43,%44,%45,%46,%47,%48,%49,%50,%51,%52,%53,%54,%55,%56,%57,%58,%59,%60,%61,%62,%63}"

template <int TB>
__device__ __forceinline__ void wgmma_rs(float (&d)[64], uint32_t a0, uint32_t a1, uint32_t a2, uint32_t a3, uint64_t db, int scale_d) {
    asm volatile("{.reg .pred p; setp.ne.b32 p, %69, 0;\n"
                 "wgmma.mma_async.sync.aligned.m64n128k16.f32.bf16.bf16 " D64 ", {%64,%65,%66,%67}, %68, p, 1, 1, %70;}\n"
                 : R64(d) : "r"(a0), "r"(a1), "r"(a2), "r"(a3), "l"(db), "r"(scale_d), "n"(TB));
}
__device__ __forceinline__ void fence_regs(float (&d)[64]) { asm volatile("" : R64(d)::"memory"); }
__device__ __forceinline__ void fence_regs(uint32_t (&d)[32]) {
#pragma unroll
    for (int i = 0; i < 32; i++) asm volatile("" : "+r"(d[i])::"memory");
}
__device__ __forceinline__ float ex2(float x) { float y; asm("ex2.approx.ftz.f32 %0, %1;" : "=f"(y) : "f"(x)); return y; }
__device__ __forceinline__ uint32_t pack_bf16(float lo, float hi) { uint32_t r; asm("cvt.rn.bf16x2.f32 %0, %1, %2;" : "=r"(r) : "f"(hi), "f"(lo)); return r; }
__device__ __forceinline__ void ldsm4(uint32_t addr, uint32_t& a, uint32_t& b, uint32_t& c, uint32_t& d) {
    asm volatile("ldmatrix.sync.aligned.m8n8.x4.shared.b16 {%0,%1,%2,%3}, [%4];" : "=r"(a), "=r"(b), "=r"(c), "=r"(d) : "r"(addr) : "memory");
}
__device__ __forceinline__ void ldsm4_if(int p, uint32_t addr, uint32_t& a, uint32_t& b, uint32_t& c, uint32_t& d) {
    asm volatile("{.reg .pred p; setp.ne.b32 p, %5, 0; @p ldmatrix.sync.aligned.m8n8.x4.shared.b16 {%0,%1,%2,%3}, [%4];}" : "+r"(a), "+r"(b), "+r"(c), "+r"(d) : "r"(addr), "r"(p) : "memory");
}
__device__ __forceinline__ void stsm4(uint32_t addr, uint32_t a, uint32_t b, uint32_t c, uint32_t d) {
    asm volatile("stmatrix.sync.aligned.m8n8.x4.shared.b16 [%4], {%0,%1,%2,%3};" ::"r"(a), "r"(b), "r"(c), "r"(d), "r"(addr) : "memory");
}

__device__ __forceinline__ int tile_qrow(int t, int cta) {
    const bool g = cta >= 64;
    const int c = cta & 63;
    const int st = ((g ? PH_START_B : PH_START_A) >> (4 * t)) & 15, lg = ((g ? PH_LOG_B : PH_LOG_A) >> (4 * t)) & 15;
    const int head = (g ? 128 : 0) + 8 * st + (c >> (3 - lg));
    const int qt = ((c & ((8 >> lg) - 1)) << lg) + (t - st);
    return head * 1024 + qt * 128;
}
#define PF_C1 4
#define PF_CL 12
#define PF_R 3
__device__ __forceinline__ void ld_pf(uint32_t dummy, const char* p) {
    if ((threadIdx.x & 31) == 0) l2_prefetch(p, 8192);
}
__device__ __forceinline__ const char* kv_piece(int v, int cta, const char* k, const char* vv) {
    const bool g = cta >= 64;
    const int c = cta & 63, t = v >> 2;
    const int st = ((g ? PH_START_B : PH_START_A) >> (4 * t)) & 15, lg = ((g ? PH_LOG_B : PH_LOG_A) >> (4 * t)) & 15;
    const int head = (g ? 128 : 0) + 8 * st + (c >> (3 - lg));
    const int x = ((v - 4 * st) << (3 - lg)) + (c & ((8 >> lg) - 1));
    return ((x & 4) ? vv : k) + (size_t)(head * 16 + (x >> 3) * 4 + (x & 3)) * 8192;
}
__device__ __forceinline__ void mma16816(float& c0, float& c1, float& c2, float& c3, uint32_t a0, uint32_t a1, uint32_t a2, uint32_t a3, uint32_t b0, uint32_t b1) {
    asm volatile("mma.sync.aligned.m16n8k16.row.col.f32.bf16.bf16.f32 {%0,%1,%2,%3}, {%4,%5,%6,%7}, {%8,%9}, {%0,%1,%2,%3};"
                 : "+f"(c0), "+f"(c1), "+f"(c2), "+f"(c3) : "r"(a0), "r"(a1), "r"(a2), "r"(a3), "r"(b0), "r"(b1));
}
__device__ __forceinline__ float rcp(float x) { float y; asm("rcp.approx.ftz.f32 %0, %1;" : "=f"(y) : "f"(x)); return y; }

constexpr float SCALE_LOG2 = 0.08838834764831845f * 1.4426950408889634f;

#define TS(w, n, i)
#define TL(w, n, i)
#define GT(i)

constexpr float L_LO = 9.094947017729282e-13f;
constexpr float L_HI = 18446744073709551616.f;
#define NS 10
#define NS0 10
#define LDQ 2
#define EARLY1 0
#define QS0 5
#define QN0 5
#define QS1 NS
#define QN1 (16 - NS)
#define CT(j, i)

__device__ __forceinline__ void ex2v(float& x) { asm volatile("ex2.approx.ftz.f32 %0, %0;" : "+f"(x)); }
__device__ __forceinline__ void addv(float& l, float x) { asm volatile("add.f32 %0, %0, %1;" : "+f"(l) : "f"(x)); }
__device__ __forceinline__ uint32_t packv(float lo, float hi) { uint32_t r; asm volatile("cvt.rn.bf16x2.f32 %0, %1, %2;" : "=r"(r) : "f"(hi), "f"(lo)); return r; }
__device__ __forceinline__ uint32_t mulpackv(float lo, float hi, float r) {
    uint32_t d;
    asm volatile("{.reg .f32 a, b; mul.f32 a, %1, %3; mul.f32 b, %2, %3; cvt.rn.bf16x2.f32 %0, b, a;}" : "=r"(d) : "f"(lo), "f"(hi), "f"(r));
    return d;
}
__device__ __forceinline__ void scale1(uint32_t& q) { asm volatile("mul.rn.bf16x2 %0, %0, %1;" : "+r"(q) : "r"(0x3E003E00u)); }
__device__ __forceinline__ uint32_t scale2(uint32_t q) { uint32_t d; asm volatile("fma.rn.bf16x2 %0, %1, %2, %1;" : "=r"(d) : "r"(q), "r"(0x3CA53CA5u)); return d; }
__device__ __forceinline__ uint32_t movm(uint32_t a) { uint32_t d; asm volatile("movmatrix.sync.aligned.m8n8.trans.b16 %0, %1;" : "=r"(d) : "r"(a)); return d; }

struct Consumer {
    float S[64], O[64];
    uint32_t P[32], Q[32], T[32];
    float l0, l1;
    uint32_t sb, qaddr, zero, clk;
    int wg;

    __device__ __forceinline__ void SB() { asm volatile("{.reg .pred q; setp.ne.u32 q, %1, 0; @q mov.u32 %0, %%clock;}" : "+r"(clk) : "r"(zero) : "memory"); }
    __device__ __forceinline__ void ldq(int s) { ldsm4((qaddr ^ ((s & 3) << 5)) + (s >> 2) * 8192, T[4 * s], T[4 * s + 1], T[4 * s + 2], T[4 * s + 3]); }
    __device__ __forceinline__ void issue_qk(int slot) {
        uint64_t dk = mkdesc(sb + SM_K + slot * BLK_BYTES, 16, 1024);
#pragma unroll
        for (int k = 0; k < 8; k++) wgmma_rs<0>(S, Q[4 * k], Q[4 * k + 1], Q[4 * k + 2], Q[4 * k + 3], dk + ((k >> 2) * 1024 + (k & 3) * 2), k != 0);
    }
    __device__ __forceinline__ void issue_pv(uint32_t (&A)[32], int slot, int acc) {
        uint64_t dv = mkdesc(sb + SM_V + slot * BLK_BYTES, 16384, 1024);
#pragma unroll
        for (int k = 0; k < 8; k++) wgmma_rs<1>(O, A[4 * k], A[4 * k + 1], A[4 * k + 2], A[4 * k + 3], dv + k * 128, k != 0 || acc);
    }
    template <bool INIT>
    __device__ __forceinline__ void sum2(int p) {
        if (p < 0) return;
        float& l = (p & 1) ? l1 : l0;
        if (INIT && p < 2) { l = S[2 * p + 1]; } else addv(l, S[2 * p + 1]);
        addv(l, S[2 * p]);
    }
    template <bool INIT>
    __device__ __forceinline__ void exp4(int g) {
        if (g < 16) { ex2v(S[4 * g]); ex2v(S[4 * g + 1]); ex2v(S[4 * g + 2]); ex2v(S[4 * g + 3]); }
        sum2<INIT>(2 * g - 3); sum2<INIT>(2 * g - 2);
        if (g == 16) sum2<INIT>(31);
    }
    __device__ __forceinline__ void packs(uint32_t (&A)[32], int b, int e) {
#pragma unroll
        for (int i = b; i < e; i++) if (i >= 0) A[i] = packv(S[2 * i], S[2 * i + 1]);
    }
    __device__ __forceinline__ void epi(int s, float r0, float r1, uint32_t (&E)[32]) {
        E[4 * s] = mulpackv(O[8 * s], O[8 * s + 1], r0); E[4 * s + 1] = mulpackv(O[8 * s + 2], O[8 * s + 3], r1);
        E[4 * s + 2] = mulpackv(O[8 * s + 4], O[8 * s + 5], r0); E[4 * s + 3] = mulpackv(O[8 * s + 6], O[8 * s + 7], r1);
        stsm4((qaddr ^ ((s & 3) << 5)) + (s >> 2) * 8192, E[4 * s], E[4 * s + 1], E[4 * s + 2], E[4 * s + 3]);
    }
    __device__ __forceinline__ void slow_tile(const char* gq, const char* gk, const char* gv, int t, float& r0, float& r1) {
        int tid;
        asm volatile("mov.u32 %0, %%tid.x;" : "=r"(tid));
        const int lane = tid & 31, row = tile_qrow(t, blockIdx.x) + (tid >> 5) * 16;
        const uint32_t* qp = (const uint32_t*)(gq + (size_t)(row + (lane >> 2)) * 256) + (lane & 3);
        const size_t ko = (size_t)((row >> 10) * 512 + (lane >> 2)) * 256 + (lane & 3) * 4;
        const uint32_t *kp = (const uint32_t*)(gk + ko), *vp = (const uint32_t*)(gv + ko);
#pragma unroll
        for (int s = 0; s < 8; s++) { P[4 * s] = qp[8 * s]; P[4 * s + 1] = qp[8 * s + 512]; P[4 * s + 2] = qp[8 * s + 4]; P[4 * s + 3] = qp[8 * s + 516]; }
#pragma unroll
        for (int i = 0; i < 64; i++) O[i] = 0.f;
        float m0 = -INFINITY, m1 = -INFINITY, s0 = 0.f, s1 = 0.f;
#pragma unroll 1
        for (int g = 0; g < 32; g++, kp += 1024, vp += 1024) {
            float x[8];
#pragma unroll
            for (int i = 0; i < 8; i++) x[i] = 0.f;
#pragma unroll
            for (int k = 0; k < 8; k++) {
                mma16816(x[0], x[1], x[2], x[3], P[4 * k], P[4 * k + 1], P[4 * k + 2], P[4 * k + 3], kp[8 * k], kp[8 * k + 4]);
                mma16816(x[4], x[5], x[6], x[7], P[4 * k], P[4 * k + 1], P[4 * k + 2], P[4 * k + 3], kp[8 * k + 512], kp[8 * k + 516]);
                if (k & 1) SB();
            }
            float x0 = fmaxf(fmaxf(x[0], x[1]), fmaxf(x[4], x[5])), x1 = fmaxf(fmaxf(x[2], x[3]), fmaxf(x[6], x[7]));
            x0 = fmaxf(x0, __shfl_xor_sync(0xffffffffu, x0, 1)); x1 = fmaxf(x1, __shfl_xor_sync(0xffffffffu, x1, 1));
            x0 = fmaxf(x0, __shfl_xor_sync(0xffffffffu, x0, 2)); x1 = fmaxf(x1, __shfl_xor_sync(0xffffffffu, x1, 2));
            x0 = fmaxf(x0, m0); x1 = fmaxf(x1, m1);
            const float a0 = ex2((m0 - x0) * SCALE_LOG2), a1 = ex2((m1 - x1) * SCALE_LOG2);
            m0 = x0; m1 = x1;
#pragma unroll
            for (int i = 0; i < 8; i++) x[i] = ex2((x[i] - ((i & 2) ? m1 : m0)) * SCALE_LOG2);
            s0 = s0 * a0 + (x[0] + x[1] + x[4] + x[5]); s1 = s1 * a1 + (x[2] + x[3] + x[6] + x[7]);
            const uint32_t p0 = pack_bf16(x[0], x[1]), p1 = pack_bf16(x[2], x[3]), p2 = pack_bf16(x[4], x[5]), p3 = pack_bf16(x[6], x[7]);
#pragma unroll
            for (int n = 0; n < 16; n++) {
                O[4 * n] *= a0; O[4 * n + 1] *= a0; O[4 * n + 2] *= a1; O[4 * n + 3] *= a1;
                mma16816(O[4 * n], O[4 * n + 1], O[4 * n + 2], O[4 * n + 3], p0, p1, p2, p3, movm(vp[4 * n]), movm(vp[4 * n + 512]));
                if ((n & 3) == 3) SB();
            }
        }
        s0 += __shfl_xor_sync(0xffffffffu, s0, 1); s1 += __shfl_xor_sync(0xffffffffu, s1, 1);
        s0 += __shfl_xor_sync(0xffffffffu, s0, 2); s1 += __shfl_xor_sync(0xffffffffu, s1, 2);
        r0 = rcp(s0); r1 = rcp(s1);
    }
    __device__ __forceinline__ void shfl_add(float& e, int m) {
        asm volatile("{.reg .f32 t; shfl.sync.bfly.b32 t, %0, %1, 0x1f, 0xffffffff; add.f32 %0, %0, t;}" : "+f"(e) : "r"(m));
    }
    __device__ __forceinline__ bool unsafe(float e0, float e1) { return __any_sync(0xffffffffu, !(e0 + e1 <= L_HI && fminf(e0, e1) >= L_LO)); }

    __device__ __forceinline__ void wait_o(uint32_t (&A)[32]) {
        wg_wait<0>();
        fence_regs(O);
        fence_regs(A);
        asm volatile("{.reg .pred q; setp.ne.u32 q, %0, 0; @q bar.arrive 5, 160;}" ::"r"(wg) : "memory");
    }
    template <int J>
    __device__ __forceinline__ void issue(uint32_t (&A)[32], int ks, int vs) {
        bar_sync(1 + wg, 288);
        CT(J, 0);
        wg_fence();
        issue_qk(ks);
        wg_commit();
        if (J == 3 && LDQ == 2) {
            bar_sync(6 + wg, 160);
#pragma unroll
            for (int s = 0; s < 8; s++) ldq(s);
        }
        issue_pv(A, vs, J != 1);
        wg_commit();
        CT(J, 1);
        if (J == 3 && LDQ == 0) {
            bar_sync(6 + wg, 160);
#pragma unroll
            for (int s = 0; s < 8; s++) ldq(s);
        }
        wg_wait<1>();
        bar_arrive(2 - wg, 288);
        fence_regs(S);
        CT(J, 2);
        SB();
    }
    template <int J, bool HEAD>
    __device__ __forceinline__ void arm(const char* gq, const char* gk, const char* gv, int t) {
        if (J == 0) {
            float e0 = l0, e1 = l1, t0, t1, r0, r1;
            bool bad;
#pragma unroll
            for (int g = 0; g <= 16; g++) {
                if (g == NS0) {
                    CT(J, 3);
                    wait_o(P);
                    CT(J, 4);
                    if (!HEAD && __builtin_expect(bad, 0)) slow_tile(gq, gk, gv, t, r0, r1);
                }
                exp4<true>(g);
                if (!HEAD) {
                    if (g == 0) { t0 = __shfl_xor_sync(0xffffffffu, e0, 1); t1 = __shfl_xor_sync(0xffffffffu, e1, 1); }
                    if (g == 3) { addv(e1, t1); addv(e0, t0); t0 = __shfl_xor_sync(0xffffffffu, e0, 2); t1 = __shfl_xor_sync(0xffffffffu, e1, 2); }
                    if (g == 6) { addv(e1, t1); addv(e0, t0); r0 = rcp(e0); r1 = rcp(e1); bad = unsafe(e0, e1); asm volatile("" : "+f"(r0), "+f"(r1)); }
                    if (g >= NS0 && g < NS0 + 4) { epi(2 * (g - NS0), r0, r1, P); epi(2 * (g - NS0) + 1, r0, r1, P); }
                }
                if (HEAD || g < NS0) packs(T, 2 * g - 3, g == 16 ? 32 : 2 * g - 1);
                else if (g >= NS0 + 4) {
                    const int b = 2 * NS0 - 3, n = 29 - b, c = g - NS0 - 4, d = 12 - NS0;
                    packs(T, b + c * n / d, g == 16 ? 32 : b + (c + 1) * n / d);
                }
                if (g < 16) SB();
            }
        } else {
#pragma unroll
            for (int g = 0; g <= 16; g++) {
                if (g == NS) { CT(J, 3); if (J == 1) wait_o(T); else wait_o(P); CT(J, 4); }
                exp4<false>(g);
                if (J == 3 && LDQ == 1 && g == 0) {
                    bar_sync(6 + wg, 160);
#pragma unroll
                    for (int s = 0; s < 8; s++) ldq(s);
                }
                if (J == 1 && EARLY1) packs(P, 2 * g - 3, g == 16 ? 32 : 2 * g - 1);
                else if (g >= NS) packs(P, (g - NS) * 29 / (16 - NS), g == 16 ? 32 : (g + 1 - NS) * 29 / (16 - NS));
                if (J == 3) {
#pragma unroll
                    for (int s = 0; s < 32; s++) {
                        if (g == QS0 + s * QN0 / 32) scale1(T[31 - s]);
                        if (g == QS1 + s * QN1 / 32) Q[31 - s] = scale2(T[31 - s]);
                    }
                }
                if (g < 16) SB();
            }
        }
        CT(J, 5);
    }
    __device__ __forceinline__ int next(int s) { return s == 2 ? 0 : s + 1; }
    __device__ __forceinline__ void run(uint32_t first, const char* gq, const char* gk, const char* gv) {
        int ks = 0, vs;
        bar_sync(6 + wg, 160);
#pragma unroll
        for (int s = 0; s < 8; s++) ldq(s);
#pragma unroll
        for (int s = 0; s < 32; s++) { scale1(T[s]); Q[s] = scale2(T[s]); }
        SB();
        bar_sync(1 + wg, 288);
        wg_fence();
        issue_qk(0);
        wg_commit();
        bar_arrive(2 - wg, 288);
        wg_wait<0>();
        fence_regs(S);
        arm<0, true>(gq, gk, gv, 0);
#pragma unroll 1
        for (int t = 0;; t++) {
            vs = ks; ks = next(ks);
            issue<1>(T, ks, vs);
            arm<1, false>(gq, gk, gv, t);
            vs = ks; ks = next(ks);
            issue<2>(P, ks, vs);
            arm<2, false>(gq, gk, gv, t);
            vs = ks; ks = next(ks);
            issue<3>(P, ks, vs);
            arm<3, false>(gq, gk, gv, t);
            if (t == NT - 1) break;
            vs = ks; if ((first >> (t + 1)) & 1) ks = next(ks);
            issue<0>(P, ks, vs);
            arm<0, false>(gq, gk, gv, t);
        }
        bar_sync(1 + wg, 288);
        wg_fence();
        issue_pv(P, ks, 1);
        wg_commit();
        if (wg == 0) bar_arrive(2, 288);
        shfl_add(l0, 1); shfl_add(l1, 1); shfl_add(l0, 2); shfl_add(l1, 2);
        float r0 = rcp(l0), r1 = rcp(l1);
        const bool bad = unsafe(l0, l1);
        wg_wait<0>();
        fence_regs(O);
        fence_regs(P);
        if (__builtin_expect(bad, 0)) slow_tile(gq, gk, gv, NT - 1, r0, r1);
#pragma unroll
        for (int s = 0; s < 8; s++) epi(s, r0, r1, P);
        bar_arrive(3 + wg + clk, 160);
    }
};

__global__ void __launch_bounds__(384, 1)
gqa_fwd_kernel(const __grid_constant__ CUtensorMap tmQ, const __grid_constant__ CUtensorMap tmK,
               const __grid_constant__ CUtensorMap tmV, const __grid_constant__ CUtensorMap tmO,
               const char* __restrict__ gq, const char* __restrict__ gk, const char* __restrict__ gv) {
    extern __shared__ char smem_raw[];
    const uint32_t sb = (smem_u32(smem_raw) + 1023) & ~1023u;
    const uint32_t bars = sb + SM_BAR;
    const int warp = __shfl_sync(0xffffffffu, threadIdx.x >> 5, 0);
    const int lane = threadIdx.x & 31;
    const int cta = blockIdx.x;
    const uint32_t first = cta >= 64 ? FIRST_B : FIRST_A;

    if (warp == 7) { TL(0, 66, 0); GT(0); }
    if (warp >= 8 && lane == 0) {
        const uint32_t b = bars + 24 * (warp - 8);
        mbar_init(b, 1); mbar_init(b + 8, 1); mbar_init(b + 16, 1);
        asm volatile("fence.mbarrier_init.release.cluster;" ::: "memory");
        asm volatile("fence.proxy.async.shared::cta;" ::: "memory");
        const int row = tile_qrow(0, cta);
        if (warp == 8) {
            mbar_expect_tx(b, BLK_BYTES);
            tma_load(sb + SM_K, &tmK, 0, (row >> 10) * 512, b);
            tma_load(sb + SM_K + 16384, &tmK, 64, (row >> 10) * 512, b);
        } else if (warp == 9) {
            asm volatile("prefetch.tensormap [%0];" ::"l"(&tmV) : "memory");
            asm volatile("prefetch.tensormap [%0];" ::"l"(&tmO) : "memory");
        } else {
            const uint32_t buf = sb + SM_Q + (warp - 10) * 16384;
            mbar_expect_tx(b, 16384);
            tma_load_h(buf, &tmQ, 0, row + (warp - 10) * 64, b, EF_Q ? POL_FIRST : POL_NORMAL);
            tma_load_h(buf + 8192, &tmQ, 64, row + (warp - 10) * 64, b, EF_Q ? POL_FIRST : POL_NORMAL);
        }
    }
    if (warp == 8) TL(0, 67, 6);
    if (warp == 11) TL(1, 67, 6);
    __syncthreads();

    if (warp >= 8) {
        asm volatile("setmaxnreg.dec.sync.aligned.u32 24;");
        if (warp < 10) {
            const bool isv = warp == 9;
            const CUtensorMap* tm = isv ? &tmV : &tmK;
            uint32_t kph = 0, vph = 0;
            int slot = 0, s1 = 0, s2 = 0, s3 = 0, flip = 0;
            const char** pft = (const char**)(smem_raw + (bars + 256 - smem_u32(smem_raw)));
            const uint32_t pfd = bars + 256 + 1024 + lane * 16;
            int pc = PF_C1;
            if (isv) {
#pragma unroll 1
                for (int k = lane; k < 62; k += 32) {
                    const int p = min(k + 4, 63);
                    pft[2 * k] = kv_piece(k + 2, cta, gk, gv);
                    pft[2 * k + 1] = gq + (size_t)(tile_qrow(p >> 2, cta) / 32 + (p & 3)) * 8192;
                }
                __syncwarp();
                TL(1, 67, 2);
            }
#pragma unroll 1
            for (int n = -2; n <= 4 * NT; n++) {
                if (n >= 0) {
                    if (!isv) {
                        if (n < 4 * NT && ((n & 3) == 3 || ((first >> (n >> 2)) & 1))) { mbar_wait_b(bars + B_KFULL + 8 * s2, (kph >> s2) & 1); kph ^= 1u << s2; }
                        TS(0, n, 2);
                        if (n > 0 && ((n & 3) == 0 || ((first >> (n >> 2)) & 1))) { mbar_wait_b(bars + B_VFULL + 8 * s3, (vph >> s3) & 1); vph ^= 1u << s3; }
                        TS(0, n, 3);
                    }
                    TS(isv, n, 0);
                    bar_sync(1 + isv, 288);
                    TS(isv, n, 1);
                    if ((n & 3) == 1 && lane == 0) mbar_arrive(bars + B_QREL + 24 * isv);
                    if (isv) {
                        const int e = min(min(PF_C1 + PF_R * (n + 1), PF_CL + 2 * n + 2), 123);
#pragma unroll
                        for (int k = 0; k < PF_R; k++) if (pc + k < e) ld_pf(pfd, pft[pc + k] + lane * 256);
                        pc = e;
                        if (n < 4 * NT) bar_sync(5, 160);
                    }
                }
                const int a = n + 2, j = a & 3;
                const bool fst = (first >> (a >> 2)) & 1;
                if (j == 0) flip = fst ? 0 : flip ^ 1;
                if (a < 4 * NT && (fst || j == 3) && (a > 0 || isv) && lane == 0) {
                    const int row = (tile_qrow(a >> 2, cta) >> 10) * 512 + (flip ? 0 : j) * 128;
                    const uint32_t full = bars + (isv ? B_VFULL : B_KFULL) + 8 * slot, buf = sb + (isv ? SM_V : SM_K) + slot * BLK_BYTES;
                    mbar_expect_tx(full, BLK_BYTES);
                    tma_load(buf, tm, 0, row, full);
                    tma_load(buf + 16384, tm, 64, row, full);
                }
                __syncwarp();
                if (n < 0) TL(isv, 67, n + 2);
                if (n == -1 && isv) {
#pragma unroll
                    for (int k = 0; k < PF_C1; k++) ld_pf(pfd, pft[k] + lane * 256);
                    TL(1, 67, 3);
                }
                s3 = s2; s2 = s1; s1 = slot;
                if (j != 3 || ((first >> ((a + 1) >> 2)) & 1)) slot = slot == 2 ? 0 : slot + 1;
            }
            asm volatile("cp.async.wait_all;" ::: "memory");
            bar_sync(3 + isv, 160);
            TS(isv, 65, 1);
            if (lane == 0) mbar_arrive(bars + B_QREL + 24 * isv);
        } else {
            const int w = warp - 10;
            const uint32_t buf = sb + SM_Q + w * 16384;
            const uint32_t full = bars + B_QFULL + 24 * w, rel = bars + B_QREL + 24 * w;
#pragma unroll 1
            for (int t = -2; t < NT; t++) {
                if (t >= -1) mbar_wait_b(rel, (t + 1) & 1);
                if (t >= -1) TS(w, 4 * t + 5, 4);
                if (lane == 0) {
                    if (t >= 0) {
                        const int row = tile_qrow(t, cta) + w * 64;
                        asm volatile("fence.proxy.async.shared::cta;" ::: "memory");
                        tma_store_h(buf, &tmO, 0, row, EF_O ? POL_FIRST : POL_NORMAL);
                        tma_store_h(buf + 8192, &tmO, 64, row, EF_O ? POL_FIRST : POL_NORMAL);
                        asm volatile("cp.async.bulk.commit_group;" ::: "memory");
                        asm volatile("cp.async.bulk.wait_group.read 0;" ::: "memory");
                    }
                    if (t >= -1 && t + 2 < NT) {
                        const int row = tile_qrow(t + 2, cta) + w * 64;
                        mbar_expect_tx(full, 16384);
                        tma_load_h(buf, &tmQ, 0, row, full, EF_Q ? POL_FIRST : POL_NORMAL);
                        tma_load_h(buf + 8192, &tmQ, 64, row, full, EF_Q ? POL_FIRST : POL_NORMAL);
                    }
                }
                __syncwarp();
                if (t >= -1) TS(w, 4 * t + 5, 5); else TL(w, 67, 4);
                if (t + 2 < NT) mbar_wait_b(full, t & 1);
                if (t + 2 <= NT) { TS(w, 4 * t + 8, 6); bar_arrive(6 + w, 160); }
            }

            if (w == 1) { TS(1, 66, 1); GT(1); }
        }
    } else {
        asm volatile("setmaxnreg.inc.sync.aligned.u32 240;");
        Consumer c;
        c.sb = sb; c.wg = warp >> 2;
        c.zero = __shfl_sync(0xffffffffu, threadIdx.y, 0); c.clk = 0;
        {
            const int row = (warp & 3) * 16 + (lane & 15);
            c.qaddr = sb + SM_Q + c.wg * 16384 + row * 128 + (((lane >> 4) ^ (row & 7)) << 4);
        }
        if (c.wg == 1) bar_arrive(1, 288);
        c.run(first, gq, gk, gv);
    }
}

typedef CUresult (*EncodeFn)(CUtensorMap*, CUtensorMapDataType, cuuint32_t, void*, const cuuint64_t*, const cuuint64_t*,
                             const cuuint32_t*, const cuuint32_t*, CUtensorMapInterleave, CUtensorMapSwizzle,
                             CUtensorMapL2promotion, CUtensorMapFloatOOBfill);

void make_map(EncodeFn enc, CUtensorMap* m, void* p, uint64_t rows, uint32_t box_rows) {
    cuuint64_t dims[2] = {128, rows};
    cuuint64_t strides[1] = {256};
    cuuint32_t box[2] = {64, box_rows};
    cuuint32_t es[2] = {1, 1};
    enc(m, CU_TENSOR_MAP_DATA_TYPE_BFLOAT16, 2, p, dims, strides, box, es, CU_TENSOR_MAP_INTERLEAVE_NONE,
        CU_TENSOR_MAP_SWIZZLE_128B, CU_TENSOR_MAP_L2_PROMOTION_L2_256B, CU_TENSOR_MAP_FLOAT_OOB_FILL_NONE);
}

}

extern "C" void kernel_launch(void* const* d_in, const int* in_sizes, int n_in, void* d_out, int out_size) {
    static EncodeFn enc = nullptr;
    if (!enc) {
        void* fn = nullptr;
        cudaDriverEntryPointQueryResult qr;
        cudaGetDriverEntryPoint("cuTensorMapEncodeTiled", &fn, cudaEnableDefault, &qr);
        enc = (EncodeFn)fn;
        cudaFuncSetAttribute(gqa_fwd_kernel, cudaFuncAttributeMaxDynamicSharedMemorySize, SM_TOTAL);
    }
    CUtensorMap tq, tk, tv, to;
    make_map(enc, &tq, d_in[0], 262144, 64);
    make_map(enc, &tk, d_in[1], 131072, 128);
    make_map(enc, &tv, d_in[2], 131072, 128);
    make_map(enc, &to, d_out, 262144, 64);
    gqa_fwd_kernel<<<NCTA, 384, SM_TOTAL>>>(tq, tk, tv, to, (const char*)d_in[0], (const char*)d_in[1], (const char*)d_in[2]);
}
```

```cpp
#include <cuda_runtime.h>
#include <cuda_bf16.h>
#include <cuda.h>
#include <stdint.h>

namespace {

constexpr int NCTA = 132;
constexpr int NT   = 16;
constexpr int NDYN = 68;
constexpr int NFULL = 12;
constexpr int BLK_BYTES = 32768;

constexpr uint64_t FIRST = 0xFE23F117D447AA8Bull;
constexpr int DYN0 = 132;
__device__ unsigned int g_ticket;

constexpr uint32_t SM_K = 0;
constexpr uint32_t SM_V = 3 * BLK_BYTES;
constexpr uint32_t SM_Q = 6 * BLK_BYTES;
constexpr uint32_t SM_BAR = 7 * BLK_BYTES;
constexpr uint32_t SM_TOTAL = SM_BAR + 256 + 1024;
constexpr uint32_t B_KFULL = 0, B_VFULL = 24, B_QFULL = 48, B_QREL = 56, B_DYN = 96;
constexpr uint32_t B_GO = 104;
constexpr uint32_t B_ROWS = 160;

__device__ __forceinline__ uint32_t smem_u32(const void* p) { return (uint32_t)__cvta_generic_to_shared(p); }
__device__ __forceinline__ void mbar_init(uint32_t bar, uint32_t cnt) { asm volatile("mbarrier.init.shared::cta.b64 [%0], %1;" ::"r"(bar), "r"(cnt)); }
__device__ __forceinline__ void mbar_arrive(uint32_t bar) { asm volatile("mbarrier.arrive.shared::cta.b64 _, [%0];" ::"r"(bar) : "memory"); }
__device__ __forceinline__ void mbar_expect_tx(uint32_t bar, uint32_t bytes) { asm volatile("mbarrier.arrive.expect_tx.shared::cta.b64 _, [%0], %1;" ::"r"(bar), "r"(bytes) : "memory"); }
__device__ __forceinline__ bool mbar_try(uint32_t bar, uint32_t parity) {
    uint32_t ok;
    asm volatile("{.reg .pred p; mbarrier.try_wait.parity.shared::cta.b64 p, [%1], %2; selp.u32 %0,1,0,p;}" : "=r"(ok) : "r"(bar), "r"(parity) : "memory");
    return ok;
}
__device__ __forceinline__ void mbar_wait_b(uint32_t bar, uint32_t parity) {
#pragma unroll 1
    for (int i = 0; i < (1 << 22); i++) { if (mbar_try(bar, parity)) return; }
    __trap();
}
__device__ __forceinline__ void mbar_wait(uint32_t bar, uint32_t parity) {
    asm volatile("{\n.reg .pred p;\nLAB_WAIT:\nmbarrier.try_wait.parity.shared::cta.b64 p, [%0], %1;\n@!p bra LAB_WAIT;\n}" ::"r"(bar), "r"(parity) : "memory");
}
__device__ __forceinline__ void tma_load(uint32_t dst, const CUtensorMap* tm, int c0, int c1, uint32_t bar) {
    asm volatile("cp.async.bulk.tensor.2d.shared::cluster.global.mbarrier::complete_tx::bytes [%0], [%1, {%3, %4}], [%2];"
                 ::"r"(dst), "l"(tm), "r"(bar), "r"(c0), "r"(c1) : "memory");
}
__device__ __forceinline__ void tma_store(uint32_t src, const CUtensorMap* tm, int c0, int c1) {
    asm volatile("cp.async.bulk.tensor.2d.global.shared::cta.bulk_group [%1, {%2, %3}], [%0];"
                 ::"r"(src), "l"(tm), "r"(c0), "r"(c1) : "memory");
}
constexpr uint64_t POL_FIRST = 0x12F0000000000000ull, POL_NORMAL = 0x1000000000000000ull;
__device__ __forceinline__ void tma_load_h(uint32_t dst, const CUtensorMap* tm, int c0, int c1, uint32_t bar, uint64_t pol) {
    asm volatile("cp.async.bulk.tensor.2d.shared::cluster.global.mbarrier::complete_tx::bytes.L2::cache_hint [%0], [%1, {%3, %4}], [%2], %5;"
                 ::"r"(dst), "l"(tm), "r"(bar), "r"(c0), "r"(c1), "l"(pol) : "memory");
}
__device__ __forceinline__ void tma_store_h(uint32_t src, const CUtensorMap* tm, int c0, int c1, uint64_t pol) {
    asm volatile("cp.async.bulk.tensor.2d.global.shared::cta.bulk_group.L2::cache_hint [%1, {%2, %3}], [%0], %4;"
                 ::"r"(src), "l"(tm), "r"(c0), "r"(c1), "l"(pol) : "memory");
}
__device__ __forceinline__ void l2_prefetch(const void* p, uint32_t bytes) {
    asm volatile("cp.async.bulk.prefetch.L2.global [%0], %1;" ::"l"(p), "r"(bytes) : "memory");
}
__device__ __forceinline__ void bar_sync(int id, int n) { asm volatile("bar.sync %0, %1;" ::"r"(id), "r"(n) : "memory"); }
__device__ __forceinline__ void bar_arrive(int id, int n) { asm volatile("bar.arrive %0, %1;" ::"r"(id), "r"(n) : "memory"); }
__device__ __forceinline__ void wg_fence() { asm volatile("wgmma.fence.sync.aligned;" ::: "memory"); }
__device__ __forceinline__ void wg_commit() { asm volatile("wgmma.commit_group.sync.aligned;" ::: "memory"); }
template <int N> __device__ __forceinline__ void wg_wait() { asm volatile("wgmma.wait_group.sync.aligned %0;" ::"n"(N) : "memory"); }

constexpr uint32_t SLOT = BLK_BYTES >> 4, KD0 = (SM_K >> 4) + (1u << 16), K2K = (1023u << 16), K2V = K2K + 3 * SLOT;

#define R8(d, o) "+f"(d[o + 0]), "+f"(d[o + 1]), "+f"(d[o + 2]), "+f"(d[o + 3]), "+f"(d[o + 4]), "+f"(d[o + 5]), "+f"(d[o + 6]), "+f"(d[o + 7])
#define R64(d) R8(d, 0), R8(d, 8), R8(d, 16), R8(d, 24), R8(d, 32), R8(d, 40), R8(d, 48), R8(d, 56)
#define D64 "{%0,%1,%2,%3,%4,%5,%6,%7,%8,%9,%10,%11,%12,%13,%14,%15,%16,%17,%18,%19,%20,%21,%22,%23,%24,%25,%26,%27,%28,%29,%30,%31,%32,%33,%34,%35,%36,%37,%38,%39,%40,%41,%42,%43,%44,%45,%46,%47,%48,%49,%50,%51,%52,%53,%54,%55,%56,%57,%58,%59,%60,%61,%62,%63}"

template <int TB>
__device__ __forceinline__ void wgmma_rs(float (&d)[64], uint32_t a0, uint32_t a1, uint32_t a2, uint32_t a3, uint64_t db, int scale_d) {
    asm volatile("{.reg .pred p; setp.ne.b32 p, %69, 0;\n"
                 "wgmma.mma_async.sync.aligned.m64n128k16.f32.bf16.bf16 " D64 ", {%64,%65,%66,%67}, %68, p, 1, 1, %70;}\n"
                 : R64(d) : "r"(a0), "r"(a1), "r"(a2), "r"(a3), "l"(db), "r"(scale_d), "n"(TB));
}
__device__ __forceinline__ void wgmma_ss(float (&d)[64], uint64_t da, uint64_t db, int scale_d) {
    asm volatile("{.reg .pred p; setp.ne.b32 p, %66, 0;\n"
                 "wgmma.mma_async.sync.aligned.m64n128k16.f32.bf16.bf16 " D64 ", %64, %65, p, 1, 1, 0, 0;}\n"
                 : R64(d) : "l"(da), "l"(db), "r"(scale_d));
}
#define D32 "{%0,%1,%2,%3,%4,%5,%6,%7,%8,%9,%10,%11,%12,%13,%14,%15,%16,%17,%18,%19,%20,%21,%22,%23,%24,%25,%26,%27,%28,%29,%30,%31}"
__device__ __forceinline__ void wgmma_rs64(float (&d)[32], uint32_t a0, uint32_t a1, uint32_t a2, uint32_t a3, uint64_t db, int scale_d) {
    asm volatile("{.reg .pred p; setp.ne.b32 p, %37, 0;\n"
                 "wgmma.mma_async.sync.aligned.m64n64k16.f32.bf16.bf16 " D32 ", {%32,%33,%34,%35}, %36, p, 1, 1, 1;}\n"
                 : R8(d, 0), R8(d, 8), R8(d, 16), R8(d, 24) : "r"(a0), "r"(a1), "r"(a2), "r"(a3), "l"(db), "r"(scale_d));
}
__device__ __forceinline__ void fence_regs(float (&d)[32]) { asm volatile("" : R8(d, 0), R8(d, 8), R8(d, 16), R8(d, 24)::"memory"); }
__device__ __forceinline__ void fence_regs(float (&d)[64]) { asm volatile("" : R64(d)::"memory"); }
__device__ __forceinline__ void fence_regs(uint32_t (&d)[32]) {
#pragma unroll
    for (int i = 0; i < 32; i++) asm volatile("" : "+r"(d[i])::"memory");
}
__device__ __forceinline__ float ex2(float x) { float y; asm("ex2.approx.ftz.f32 %0, %1;" : "=f"(y) : "f"(x)); return y; }
__device__ __forceinline__ uint32_t pack_bf16(float lo, float hi) { uint32_t r; asm("cvt.rn.bf16x2.f32 %0, %1, %2;" : "=r"(r) : "f"(hi), "f"(lo)); return r; }
__device__ __forceinline__ void ldsm4(uint32_t addr, uint32_t& a, uint32_t& b, uint32_t& c, uint32_t& d) {
    asm volatile("ldmatrix.sync.aligned.m8n8.x4.shared.b16 {%0,%1,%2,%3}, [%4];" : "=r"(a), "=r"(b), "=r"(c), "=r"(d) : "r"(addr) : "memory");
}
__device__ __forceinline__ void ldsm4_if(int p, uint32_t addr, uint32_t& a, uint32_t& b, uint32_t& c, uint32_t& d) {
    asm volatile("{.reg .pred p; setp.ne.b32 p, %5, 0; @p ldmatrix.sync.aligned.m8n8.x4.shared.b16 {%0,%1,%2,%3}, [%4];}" : "+r"(a), "+r"(b), "+r"(c), "+r"(d) : "r"(addr), "r"(p) : "memory");
}
__device__ __forceinline__ void stsm4(uint32_t addr, uint32_t a, uint32_t b, uint32_t c, uint32_t d) {
    asm volatile("stmatrix.sync.aligned.m8n8.x4.shared.b16 [%4], {%0,%1,%2,%3};" ::"r"(a), "r"(b), "r"(c), "r"(d), "r"(addr) : "memory");
}

__device__ __forceinline__ uint32_t first_mask(int cta) { return (FIRST >> (max(cta - 4, 0) >> 5 << 4)) & 0xFFFF; }
__device__ __forceinline__ int tile_index(int t, int cta) {
    const uint32_t f = first_mask(cta);
    const int c0 = cta < 36 ? 0 : ((cta - 4) & ~31) + 4, t0 = 31 - __clz(f & ((2u << t) - 1)), len = __ffs(f >> (t0 + 1));
    return t == 0 ? cta : 200 + 14 * c0 + (cta < 36 ? 36 : 32) * (t0 - 1) + (cta - c0) * len + t - t0;
}
__device__ __forceinline__ int lds(uint32_t a) { int v; asm volatile("ld.shared.s32 %0, [%1];" : "=r"(v) : "r"(a) : "memory"); return v; }
__device__ __forceinline__ void sts(uint32_t a, int v) { asm volatile("st.shared.s32 [%0], %1;" ::"r"(a), "r"(v) : "memory"); }
__device__ __forceinline__ void ahead(const char* g, uint32_t bars, uint32_t first, int t, int j) {
    if ((first >> t) & 1) {
        const int r = lds(bars + B_ROWS + 4 * t);
        l2_prefetch(g + ((r >> 10) * 131072 + j * 32768 + (r & 1023) * 32), __ffs(first >> (t + 1)) * 4096);
    }
}
__device__ __forceinline__ void mma16816(float& c0, float& c1, float& c2, float& c3, uint32_t a0, uint32_t a1, uint32_t a2, uint32_t a3, uint32_t b0, uint32_t b1) {
    asm volatile("mma.sync.aligned.m16n8k16.row.col.f32.bf16.bf16.f32 {%0,%1,%2,%3}, {%4,%5,%6,%7}, {%8,%9}, {%0,%1,%2,%3};"
                 : "+f"(c0), "+f"(c1), "+f"(c2), "+f"(c3) : "r"(a0), "r"(a1), "r"(a2), "r"(a3), "r"(b0), "r"(b1));
}
__device__ __forceinline__ float rcp(float x) { float y; asm("rcp.approx.ftz.f32 %0, %1;" : "=f"(y) : "f"(x)); return y; }

constexpr float SCALE_LOG2 = 0.08838834764831845f * 1.4426950408889634f;

constexpr float L_LO = 9.094947017729282e-13f;
constexpr float L_HI = 18446744073709551616.f;
constexpr int NS = 9;
constexpr int NS0 = 10, QS0 = 5, QN0 = 5, QS1 = NS, QN1 = 16 - NS;

__device__ __forceinline__ void ex2v(float& x) { asm volatile("ex2.approx.ftz.f32 %0, %0;" : "+f"(x)); }
__device__ __forceinline__ void addv(float& l, float x) { asm volatile("add.f32 %0, %0, %1;" : "+f"(l) : "f"(x)); }
__device__ __forceinline__ uint32_t packv(float lo, float hi) { uint32_t r; asm volatile("cvt.rn.bf16x2.f32 %0, %1, %2;" : "=r"(r) : "f"(hi), "f"(lo)); return r; }
__device__ __forceinline__ uint32_t mulpackv(float lo, float hi, float r) {
    uint32_t d;
    asm volatile("{.reg .f32 a, b; mul.f32 a, %1, %3; mul.f32 b, %2, %3; cvt.rn.bf16x2.f32 %0, b, a;}" : "=r"(d) : "f"(lo), "f"(hi), "f"(r));
    return d;
}
__device__ __forceinline__ void scale1(uint32_t& q) { asm volatile("mul.rn.bf16x2 %0, %0, %1;" : "+r"(q) : "r"(0x3E003E00u)); }
__device__ __forceinline__ uint32_t scale2(uint32_t q) { uint32_t d; asm volatile("fma.rn.bf16x2 %0, %1, %2, %1;" : "=r"(d) : "r"(q), "r"(0x3CA53CA5u)); return d; }
__device__ __forceinline__ uint32_t movm(uint32_t a) { uint32_t d; asm volatile("movmatrix.sync.aligned.m8n8.trans.b16 %0, %1;" : "=r"(d) : "r"(a)); return d; }

struct Consumer {
    float S[64], O[64];
    uint32_t P[32], Q[32], T[32];
    float l0, l1;
    uint32_t sb, qaddr, zero, kd, vd, first;
    int wg, nxt, vrel;

    __device__ __forceinline__ void SB() { asm volatile("{.reg .pred q; setp.ne.u32 q, %0, 0; @q griddepcontrol.launch_dependents;}" ::"r"(zero) : "memory"); }
    __device__ __forceinline__ void ldq(int s) { ldsm4((qaddr ^ ((s & 3) << 5)) + (s >> 2) * 8192, T[4 * s], T[4 * s + 1], T[4 * s + 2], T[4 * s + 3]); }
    __device__ __forceinline__ uint64_t desc(uint32_t lo) { uint64_t d; asm("mov.b64 %0, {%1, %2};" : "=l"(d) : "r"(lo), "r"(0x40000040u)); return d; }
    __device__ __forceinline__ uint32_t next(uint32_t d) { return d + (d >= (sb >> 4) + KD0 + 2 * SLOT ? -2 * SLOT : SLOT); }
    template <int J>
    __device__ __forceinline__ void advance() {
        vd = kd + K2V;
        if (J == 1) { first >>= 1; vrel = first & wg; }
        if (J != 3 || (first & 1)) kd = next(kd);
        if ((J == 0 && (nxt & 1)) || (J == 3 && (nxt & wg))) kd = next(kd);
        asm volatile("" : "+r"(kd), "+r"(vd), "+r"(vrel));
    }
    __device__ __forceinline__ void issue_qk() {
        const uint64_t dk = desc(kd);
#pragma unroll
        for (int k = 0; k < 8; k++) wgmma_rs<0>(S, Q[4 * k], Q[4 * k + 1], Q[4 * k + 2], Q[4 * k + 3], dk + ((k >> 2) * 1024 + (k & 3) * 2), k != 0);
    }
    __device__ __forceinline__ void issue_pv(uint32_t (&A)[32], int acc) {
        const uint64_t dv = desc(vd);
#pragma unroll
        for (int k = 0; k < 8; k++) wgmma_rs<1>(O, A[4 * k], A[4 * k + 1], A[4 * k + 2], A[4 * k + 3], dv + k * 128, k != 0 || acc);
    }
    template <bool INIT>
    __device__ __forceinline__ void sum2(int p) {
        if (p < 0) return;
        float& l = (p & 1) ? l1 : l0;
        if (INIT && p < 2) { l = S[2 * p + 1]; } else addv(l, S[2 * p + 1]);
        addv(l, S[2 * p]);
    }
    template <bool INIT>
    __device__ __forceinline__ void exp4(int g) {
        if (g < 16) { ex2v(S[4 * g]); ex2v(S[4 * g + 1]); ex2v(S[4 * g + 2]); ex2v(S[4 * g + 3]); }
        sum2<INIT>(2 * g - 3); sum2<INIT>(2 * g - 2);
        if (g == 16) sum2<INIT>(31);
    }
    __device__ __forceinline__ void mul4(int g) {
#pragma unroll
        for (int i = g ? 4 * g + 4 : 0; i < 4 * g + 8 && i < 64; i++) asm volatile("mul.f32 %0, %0, %1;" : "+f"(S[i]) : "f"(SCALE_LOG2));
    }
    __device__ __forceinline__ void packs(uint32_t (&A)[32], int b, int e) {
#pragma unroll
        for (int i = b; i < e; i++) if (i >= 0) A[i] = packv(S[2 * i], S[2 * i + 1]);
    }
    __device__ __forceinline__ void epi(int s, float r0, float r1, uint32_t (&E)[32]) {
        E[4 * s] = mulpackv(O[8 * s], O[8 * s + 1], r0); E[4 * s + 1] = mulpackv(O[8 * s + 2], O[8 * s + 3], r1);
        E[4 * s + 2] = mulpackv(O[8 * s + 4], O[8 * s + 5], r0); E[4 * s + 3] = mulpackv(O[8 * s + 6], O[8 * s + 7], r1);
        stsm4((qaddr ^ ((s & 3) << 5)) + (s >> 2) * 8192, E[4 * s], E[4 * s + 1], E[4 * s + 2], E[4 * s + 3]);
    }
    __device__ __forceinline__ void slow_tile(const char* gq, const char* gk, const char* gv, int t, float& r0, float& r1) {
        int tid;
        asm volatile("mov.u32 %0, %%tid.x;" : "=r"(tid));
        const int lane = tid & 31, row = (lds(sb + SM_BAR + B_ROWS + 4 * t) & ~1) + (tid >> 5) * 16;
        const uint32_t* qp = (const uint32_t*)(gq + (size_t)(row + (lane >> 2)) * 256) + (lane & 3);
        const size_t ko = (size_t)((row >> 10) * 512 + (lane >> 2)) * 256 + (lane & 3) * 4;
        const uint32_t *kp = (const uint32_t*)(gk + ko), *vp = (const uint32_t*)(gv + ko);
#pragma unroll
        for (int s = 0; s < 8; s++) { P[4 * s] = qp[8 * s]; P[4 * s + 1] = qp[8 * s + 512]; P[4 * s + 2] = qp[8 * s + 4]; P[4 * s + 3] = qp[8 * s + 516]; }
#pragma unroll
        for (int i = 0; i < 64; i++) O[i] = 0.f;
        float m0 = -INFINITY, m1 = -INFINITY, s0 = 0.f, s1 = 0.f;
#pragma unroll 1
        for (int g = 0; g < 32; g++, kp += 1024, vp += 1024) {
            float x[8];
#pragma unroll
            for (int i = 0; i < 8; i++) x[i] = 0.f;
#pragma unroll
            for (int k = 0; k < 8; k++) {
                mma16816(x[0], x[1], x[2], x[3], P[4 * k], P[4 * k + 1], P[4 * k + 2], P[4 * k + 3], kp[8 * k], kp[8 * k + 4]);
                mma16816(x[4], x[5], x[6], x[7], P[4 * k], P[4 * k + 1], P[4 * k + 2], P[4 * k + 3], kp[8 * k + 512], kp[8 * k + 516]);
                if (k & 1) SB();
            }
            float x0 = fmaxf(fmaxf(x[0], x[1]), fmaxf(x[4], x[5])), x1 = fmaxf(fmaxf(x[2], x[3]), fmaxf(x[6], x[7]));
            x0 = fmaxf(x0, __shfl_xor_sync(0xffffffffu, x0, 1)); x1 = fmaxf(x1, __shfl_xor_sync(0xffffffffu, x1, 1));
            x0 = fmaxf(x0, __shfl_xor_sync(0xffffffffu, x0, 2)); x1 = fmaxf(x1, __shfl_xor_sync(0xffffffffu, x1, 2));
            x0 = fmaxf(x0, m0); x1 = fmaxf(x1, m1);
            const float a0 = ex2((m0 - x0) * SCALE_LOG2), a1 = ex2((m1 - x1) * SCALE_LOG2);
            m0 = x0; m1 = x1;
#pragma unroll
            for (int i = 0; i < 8; i++) x[i] = ex2((x[i] - ((i & 2) ? m1 : m0)) * SCALE_LOG2);
            s0 = s0 * a0 + (x[0] + x[1] + x[4] + x[5]); s1 = s1 * a1 + (x[2] + x[3] + x[6] + x[7]);
            const uint32_t p0 = pack_bf16(x[0], x[1]), p1 = pack_bf16(x[2], x[3]), p2 = pack_bf16(x[4], x[5]), p3 = pack_bf16(x[6], x[7]);
#pragma unroll
            for (int n = 0; n < 16; n++) {
                O[4 * n] *= a0; O[4 * n + 1] *= a0; O[4 * n + 2] *= a1; O[4 * n + 3] *= a1;
                mma16816(O[4 * n], O[4 * n + 1], O[4 * n + 2], O[4 * n + 3], p0, p1, p2, p3, movm(vp[4 * n]), movm(vp[4 * n + 512]));
                if ((n & 3) == 3) SB();
            }
        }
        s0 += __shfl_xor_sync(0xffffffffu, s0, 1); s1 += __shfl_xor_sync(0xffffffffu, s1, 1);
        s0 += __shfl_xor_sync(0xffffffffu, s0, 2); s1 += __shfl_xor_sync(0xffffffffu, s1, 2);
        r0 = rcp(s0); r1 = rcp(s1);
    }
    __device__ __forceinline__ void shfl_add(float& e, int m) {
        asm volatile("{.reg .f32 t; shfl.sync.bfly.b32 t, %0, %1, 0x1f, 0xffffffff; add.f32 %0, %0, t;}" : "+f"(e) : "r"(m));
    }
    __device__ __forceinline__ bool unsafe(float e0, float e1) {
        return __any_sync(0xffffffffu, !(e0 + e1 <= L_HI && fminf(e0, e1) >= L_LO)); }

    template <int J>
    __device__ __forceinline__ void wait_o(uint32_t (&A)[32]) {
        wg_wait<0>();
        fence_regs(O);
        fence_regs(A);
        asm volatile("{.reg .pred q; setp.ne.u32 q, %0, 0; @q bar.arrive %1, 160;}" ::"r"(J == 1 ? wg : vrel), "n"(8 + J) : "memory");
    }
    __device__ __forceinline__ void signal(uint32_t bar) {
        __syncwarp();
        asm volatile("{.reg .pred q; elect.sync _|q, 0xffffffff; @q mbarrier.arrive.shared::cta.b64 _, [%0];}" ::"r"(sb + SM_BAR + bar + 24 * wg) : "memory");
    }
    __device__ __forceinline__ void turn_wait() { asm volatile("{.reg .pred q; setp.ne.u32 q, %0, 0; @q bar.sync 2, 288; @!q bar.sync 1, 288;}" ::"r"(wg) : "memory"); }
    __device__ __forceinline__ void turn_pass() { asm volatile("{.reg .pred q; setp.ne.u32 q, %0, 0; @q bar.arrive 1, 288; @!q bar.arrive 2, 288;}" ::"r"(wg) : "memory"); }
    template <int J>
    __device__ __forceinline__ void issue(uint32_t (&A)[32]) {
        turn_wait();
        wg_fence();
        issue_qk();
        wg_commit();
        if (J == 3) {
            bar_sync(6 + wg, 160);
#pragma unroll
            for (int s = 0; s < 8; s++) ldq(s);
        }
        issue_pv(A, J != 1);
        wg_commit();
        wg_wait<1>();
        turn_pass();
        fence_regs(S);
        SB();
    }
    template <int J, bool HEAD>
    __device__ __forceinline__ void arm(const char* gq, const char* gk, const char* gv, int t) {
        if (J == 0) {
            float e0 = l0, e1 = l1, t0, t1, r0, r1;
            bool bad;
#pragma unroll
            for (int g = 0; g < NS0; g++) {
                if (HEAD) mul4(g);
                exp4<true>(g);
                if (!HEAD) {
                    if (g == 0) { t0 = __shfl_xor_sync(0xffffffffu, e0, 1); t1 = __shfl_xor_sync(0xffffffffu, e1, 1); }
                    if (g == 3) { addv(e1, t1); addv(e0, t0); t0 = __shfl_xor_sync(0xffffffffu, e0, 2); t1 = __shfl_xor_sync(0xffffffffu, e1, 2); }
                    if (g == 6) { addv(e1, t1); addv(e0, t0); r0 = rcp(e0); r1 = rcp(e1); bad = unsafe(e0, e1); asm volatile("" : "+f"(r0), "+f"(r1)); }
                }
                packs(T, 2 * g - 3, 2 * g - 1);
                if (g == 1) advance<0>();
                SB();
            }
            wait_o<0>(P);
            if (!HEAD && __builtin_expect(bad, 0)) slow_tile(gq, gk, gv, t, r0, r1);
#pragma unroll
            for (int g = NS0; g <= 16; g++) {
                if (HEAD) mul4(g);
                exp4<true>(g);
                if (HEAD) packs(T, 2 * g - 3, g == 16 ? 32 : 2 * g - 1);
                else if (g < NS0 + 4) {
                    epi(2 * (g - NS0), r0, r1, P); epi(2 * (g - NS0) + 1, r0, r1, P);
                    if (g == NS0 + 3) signal(B_QREL);
                } else {
                    const int b = 2 * NS0 - 3, n = 29 - b, c = g - NS0 - 4, d = 12 - NS0;
                    packs(T, b + c * n / d, g == 16 ? 32 : b + (c + 1) * n / d);
                }
                if (g < 16) SB();
            }
        } else {
#pragma unroll
            for (int g = 0; g <= 16; g++) {
                if (g == NS) { if (J == 1) wait_o<J>(T); else wait_o<J>(P); }
                exp4<false>(g);
                if (g >= NS) packs(P, (g - NS) * 29 / (16 - NS), g == 16 ? 32 : (g + 1 - NS) * 29 / (16 - NS));
                if (g == (J == 1 ? NS + 1 : J == 2 ? 1 : 5)) advance<J>();
                if (J == 3) {
                    if (g == 1) nxt = lds(sb + SM_BAR + B_ROWS + 4 + 4 * t);
                    if (g == 3) nxt = __shfl_sync(0xffffffffu, nxt, 0);
#pragma unroll
                    for (int s = 0; s < 32; s++) {
                        if (g == QS0 + s * QN0 / 32) scale1(T[31 - s]);
                        if (g == QS1 + s * QN1 / 32) Q[31 - s] = scale2(T[31 - s]);
                    }
                }
                if (g < 16) SB();
            }
        }
    }
    __device__ __forceinline__ void out4(int h, uint32_t a, char* g) {
        uint32_t x[16];
        __syncwarp();
#pragma unroll
        for (int i = 0; i < 4; i++) asm volatile("ld.shared.v4.u32 {%0, %1, %2, %3}, [%4];" : "=r"(x[4 * i]), "=r"(x[4 * i + 1]), "=r"(x[4 * i + 2]), "=r"(x[4 * i + 3]) : "r"((a ^ ((i & 1) << 6)) + i * 512 + h * 8192) : "memory");
#pragma unroll
        for (int i = 0; i < 4; i++) asm volatile("st.global.v4.u32 [%4], {%0, %1, %2, %3};" ::"r"(x[4 * i]), "r"(x[4 * i + 1]), "r"(x[4 * i + 2]), "r"(x[4 * i + 3]), "l"(g + i * 1024 + h * 128) : "memory");
    }
    __device__ __forceinline__ void put8(int h, uint32_t a) {
#pragma unroll
        for (int i = 8 * h; i < 8 * h + 8; i++) asm volatile("st.shared.v4.f32 [%0], {%1, %2, %3, %4};" ::"r"(a + i * 2048), "f"(O[4 * i]), "f"(O[4 * i + 1]), "f"(O[4 * i + 2]), "f"(O[4 * i + 3]) : "memory");
        bar_arrive(3 + h, 256);
    }
    __device__ __forceinline__ void get8(int h, uint32_t a, uint32_t (&A)[32]) {
        bar_sync(3 + h, 256);
#pragma unroll
        for (int i = 0; i < 8; i++) asm volatile("ld.shared.v4.u32 {%0, %1, %2, %3}, [%4];" : "=r"(A[4 * i]), "=r"(A[4 * i + 1]), "=r"(A[4 * i + 2]), "=r"(A[4 * i + 3]) : "r"(a + (i + 8 * h) * 2048) : "memory");
    }
    template <bool GIVE, bool TAKE>
    __device__ __forceinline__ void tail(const char* gq, const char* gk, const char* gv, char* go, int t, uint32_t ks) {
        float t0, t1;
        int tid;
        asm volatile("mov.u32 %0, %%tid.x;" : "=r"(tid));
        if (!GIVE && !TAKE) { t0 = __shfl_xor_sync(0xffffffffu, l0, 1); t1 = __shfl_xor_sync(0xffffffffu, l1, 1); }
        turn_wait();
        wg_fence();
        float X0[32], X1[32];
        const uint64_t dv = desc(vd);
#pragma unroll
        for (int k = 0; k < 8; k++) wgmma_rs64(X0, Q[4 * k], Q[4 * k + 1], Q[4 * k + 2], Q[4 * k + 3], dv + k * 128, k != 0);
        wg_commit();
        SB();
        const uint32_t a = (ks + (tid & 127)) * 16, la = sb + SM_Q + (tid & 127) * 8;
        int row;
        if (GIVE) asm volatile("st.shared.v2.f32 [%0], {%1, %2};" ::"r"(la), "f"(l0), "f"(l1) : "memory");
        else {
            if (TAKE) asm volatile("ld.shared.v2.f32 {%0, %1}, [%2];" : "=f"(t0), "=f"(t1) : "r"(la) : "memory");
            row = lds(sb + SM_BAR + B_ROWS + 4 * t);
            asm volatile("ld.shared.u64 %0, [%1];" : "=l"(go) : "r"(sb + SM_BAR + B_GO) : "memory");
            if (TAKE) get8(0, a, T);
            addv(l0, t0); addv(l1, t1);
            t0 = __shfl_xor_sync(0xffffffffu, l0, 2); t1 = __shfl_xor_sync(0xffffffffu, l1, 2);
        }
        SB();
        wg_fence();
#pragma unroll
        for (int k = 0; k < 8; k++) wgmma_rs64(X1, Q[4 * k], Q[4 * k + 1], Q[4 * k + 2], Q[4 * k + 3], dv + k * 128 + 1024, k != 0);
        wg_commit();
        if (!TAKE && wg == 0) bar_arrive(2, 288);
        float r0, r1;
        bool bad;
        if (!GIVE) {
            addv(l0, t0); addv(l1, t1);
            if (TAKE) {
                t0 = __shfl_xor_sync(0xffffffffu, l0, 1); t1 = __shfl_xor_sync(0xffffffffu, l1, 1);
#pragma unroll
                for (int i = 0; i < 32; i++) addv(O[i], __uint_as_float(T[i]));
                addv(l0, t0); addv(l1, t1);
            }
            r0 = rcp(l0); r1 = rcp(l1);
            bad = unsafe(l0, l1);
        }
        const int r = (tid >> 5) * 16 + ((tid >> 3) & 3);
        const uint32_t oa = sb + SM_Q + (r >> 6) * 16384 + (r & 63) * 128 + ((tid ^ r) & 7) * 16;
        char* const g = go + (size_t)((row & ~1) + r) * 256 + (tid & 7) * 16;
        wg_wait<1>();
        fence_regs(X0);
#pragma unroll
        for (int i = 0; i < 32; i++) addv(O[i], X0[i]);
        if (GIVE) put8(0, a);
        else {
            if (TAKE) get8(1, a, P);
#pragma unroll
            for (int s = 0; s < 4; s++) epi(s, r0, r1, T);
            out4(0, oa, g);
        }
        if (TAKE) {
#pragma unroll
            for (int i = 0; i < 32; i++) addv(O[32 + i], __uint_as_float(P[i]));
        }
        wg_wait<0>();
        fence_regs(X1);
        fence_regs(Q);
#pragma unroll
        for (int i = 0; i < 32; i++) addv(O[32 + i], X1[i]);
        if (GIVE) put8(1, a);
        else {
            if (__builtin_expect(bad, 0)) {
                slow_tile(gq, gk, gv, t, r0, r1);
#pragma unroll
                for (int s = 0; s < 4; s++) epi(s, r0, r1, T);
                out4(0, oa, g);
            }
#pragma unroll
            for (int s = 4; s < 8; s++) epi(s, r0, r1, T);
            out4(1, oa, g);
        }
        signal(B_QREL);
    }
    __device__ __forceinline__ void get1(int i, uint32_t a, uint32_t (&A)[32]) {
        asm volatile("ld.shared.v4.u32 {%0, %1, %2, %3}, [%4];" : "=r"(A[4 * i]), "=r"(A[4 * i + 1]), "=r"(A[4 * i + 2]), "=r"(A[4 * i + 3]) : "r"(a + i * 2048) : "memory");
    }
    template <bool GIVE, bool TAKE>
    __device__ __forceinline__ void tail2(const char* gq, const char* gk, const char* gv, char* go, int t, uint32_t ks) {
        float t0, t1;
        int tid;
        asm volatile("mov.u32 %0, %%tid.x;" : "=r"(tid));
        t0 = __shfl_xor_sync(0xffffffffu, l0, 1); t1 = __shfl_xor_sync(0xffffffffu, l1, 1);
        asm volatile("" : "+r"(tid));
        const uint32_t a = (ks + (tid & 127)) * 16, la = sb + SM_Q + (tid & 127) * 8;
        int row;
        if (!GIVE) {
            row = lds(sb + SM_BAR + B_ROWS + 4 * t);
            asm volatile("ld.shared.u64 %0, [%1];" : "=l"(go) : "r"(sb + SM_BAR + B_GO) : "memory");
        }
        turn_wait();
        float r0, r1, u0, u1;
        bool bad;
        addv(l0, t0); addv(l1, t1);
        t0 = __shfl_xor_sync(0xffffffffu, l0, 2); t1 = __shfl_xor_sync(0xffffffffu, l1, 2);
        if (GIVE) { addv(l0, t0); addv(l1, t1); asm volatile("st.shared.v2.f32 [%0], {%1, %2};" ::"r"(la), "f"(l0), "f"(l1) : "memory"); }
        if (TAKE) asm volatile("ld.shared.v2.f32 {%0, %1}, [%2];" : "=f"(u0), "=f"(u1) : "r"(la) : "memory");
        const uint64_t dv = desc(vd);
        SB();
        wg_fence();
#pragma unroll
        for (int k = 0; k < 8; k++) {
            wgmma_rs<1>(O, Q[4 * k], Q[4 * k + 1], Q[4 * k + 2], Q[4 * k + 3], dv + k * 128, 1);
        }
        wg_commit();
        if (!TAKE && wg == 0) bar_arrive(2, 288);
        SB();
        if (!GIVE) {
            addv(l0, t0); addv(l1, t1);
            if (TAKE) { addv(l0, u0); addv(l1, u1); }
            r0 = rcp(l0); r1 = rcp(l1);
            bad = unsafe(l0, l1);
        }
        const int r = (tid >> 5) * 16 + ((tid >> 3) & 3);
        uint32_t oa = sb + SM_Q + (r >> 6) * 16384 + (r & 63) * 128 + ((tid ^ r) & 7) * 16;
        char* g = go + (size_t)((row & ~1) + r) * 256 + (tid & 7) * 16;
        if (!GIVE) asm volatile("" : "+r"(oa), "+l"(g), "+f"(r0), "+f"(r1));
        if (TAKE) {
            SB();
            bar_sync(3, 256);
#pragma unroll
            for (int k = 0; k < 8; k++) get1(k, a, T);
            bar_sync(4, 256);
#pragma unroll
            for (int k = 0; k < 8; k++) get1(k, a + 16384, P);
        }
        SB();
        wg_wait<0>();
        fence_regs(O);
        fence_regs(Q);
#pragma unroll
        for (int i = 0; i < 32; i++) { if (TAKE) addv(O[i], __uint_as_float(T[i])); }
        if (GIVE) put8(0, a);
        else {
#pragma unroll
            for (int s = 0; s < 4; s++) epi(s, r0, r1, T);
            out4(0, oa, g);
            SB();
        }
#pragma unroll
        for (int i = 0; i < 32; i++) { if (TAKE) addv(O[32 + i], __uint_as_float(P[i])); }
        if (GIVE) put8(1, a);
        else {
#pragma unroll
            for (int s = 4; s < 8; s++) epi(s, r0, r1, T);
            out4(1, oa, g);
        }
        signal(B_QREL);
        if (!GIVE && __builtin_expect(bad, 0)) {
            slow_tile(gq, gk, gv, t, r0, r1);
#pragma unroll
            for (int s = 0; s < 8; s++) epi(s, r0, r1, T);
            out4(0, oa, g);
            out4(1, oa, g);
        }
    }
    template <int J>
    __device__ __forceinline__ void last(uint32_t (&A)[32]) {
        issue<J>(A);
#pragma unroll
        for (int g = 0; g <= 16; g++) {
            if (g == 12) { wait_o<J>(A); bar_sync(6 + wg, 160); }
            exp4<false>(g);
            packs(Q, 2 * g - 3, g == 16 ? 32 : 2 * g - 1);
            if (g == 1) advance<2>();
            if (g < 16) SB();
        }
    }
    __device__ __forceinline__ void run(const char* gq, const char* gk, const char* gv, char* go) {
        kd = (sb >> 4) + KD0; nxt = 0;
        mbar_wait(sb + SM_BAR + B_QFULL + 24 * wg, 0);
        mbar_wait(sb + SM_BAR + B_KFULL, 0);
        asm volatile("{.reg .pred q; setp.ne.u32 q, %0, 0; @q bar.sync 2, 288;}" ::"r"(wg) : "memory");
        wg_fence();
        {
            const uint64_t dk = desc(kd), dq = desc(kd + (SM_Q >> 4) + wg * 1024);
#pragma unroll
            for (int k = 0; k < 8; k++) wgmma_ss(S, dq + ((k >> 2) * 512 + (k & 3) * 2), dk + ((k >> 2) * 1024 + (k & 3) * 2), k != 0);
        }
        wg_commit();
        asm volatile("{.reg .pred q; setp.eq.u32 q, %0, 0; @q bar.arrive 2, 288; @q bar.sync 1, 288;}" ::"r"(wg) : "memory");
        bar_sync(6 + wg, 160);
#pragma unroll
        for (int s = 0; s < 8; s++) ldq(s);
#pragma unroll
        for (int s = 0; s < 32; s++) { scale1(T[s]); Q[s] = scale2(T[s]); }
        SB();
        vrel = wg;
        wg_wait<0>();
        asm volatile("{.reg .pred q; setp.ne.u32 q, %0, 0; @q bar.arrive 1, 288;}" ::"r"(wg) : "memory");
        fence_regs(S);
        signal(B_QREL);
        arm<0, true>(gq, gk, gv, 0);
        int t = 0;
#pragma unroll 1
        for (;; t++) {
            if (nxt & 1) {
                last<1>(T);
                kd = next(kd);
                if (wg == 0) { const uint32_t ks = (vd & 0xFFFF) - 3 * SLOT; vd = kd + K2K; tail2<true, false>(gq, gk, gv, go, t, ks); }
                else { vd = kd + K2V; tail2<false, true>(gq, gk, gv, go, t, kd & 0xFFFF); }
                return;
            }
            issue<1>(T);
            arm<1, false>(gq, gk, gv, t);
            issue<2>(P);
            arm<2, false>(gq, gk, gv, t);
            if (!first) { last<2>(P); break; }
            issue<3>(P);
            arm<3, false>(gq, gk, gv, t);
            if (nxt < 0) {
#pragma unroll
                for (int i = 0; i < 32; i++) asm volatile("mov.b32 %0, %1;" : "=r"(Q[i]) : "r"(P[i]));
                break;
            }
            issue<0>(P);
            arm<0, false>(gq, gk, gv, t);
        }
        tail<false, false>(gq, gk, gv, go, t, 0);
    }
};

__global__ void __launch_bounds__(384, 1)
gqa_fwd_kernel(const __grid_constant__ CUtensorMap tmQ, const __grid_constant__ CUtensorMap tmK,
               const __grid_constant__ CUtensorMap tmV, const __grid_constant__ CUtensorMap tmO,
               const char* __restrict__ gq, const char* __restrict__ gk, const char* __restrict__ gv, char* __restrict__ go) {
    extern __shared__ char smem_raw[];
    const uint32_t sb = (smem_u32(smem_raw) + 1023) & ~1023u;
    const uint32_t bars = sb + SM_BAR;
    const int warp = __shfl_sync(0xffffffffu, threadIdx.x >> 5, 0);
    const int lane = threadIdx.x & 31;
    const int cta = blockIdx.x;
    if (threadIdx.x == 0) {
        l2_prefetch(gk + (size_t)(cta >> 3) * 131072 + (cta & 7) * (cta < 128 ? 4096 : 8192), cta < 128 ? 4096 : 8192);
        l2_prefetch(gq + (size_t)cta * 32768, 12288);
    }
    const uint32_t first = first_mask(cta);
    if (warp >= 8 && lane == 0) {
        const uint32_t b = bars + 24 * (warp - 8);
        mbar_init(b, 1); mbar_init(b + 8, warp < 10 ? 1 : 4); mbar_init(b + 16, 1);
        if (warp == 9) mbar_init(bars + B_DYN, 1);
        asm volatile("fence.mbarrier_init.release.cluster;" ::: "memory");
        asm volatile("fence.proxy.async.shared::cta;" ::: "memory");
        const int row = cta * 128;
        if (warp == 8) {
            mbar_expect_tx(b, BLK_BYTES);
            tma_load(sb + SM_K, &tmK, 0, (row >> 10) * 512, b);
            tma_load(sb + SM_K + 16384, &tmK, 64, (row >> 10) * 512, b);
        } else if (warp == 9) {
            asm volatile("prefetch.tensormap [%0];" ::"l"(&tmV) : "memory");
            asm volatile("prefetch.tensormap [%0];" ::"l"(&tmO) : "memory");
        } else if (warp == 10) {
            const uint32_t buf = sb + SM_Q + (warp - 10) * 16384;
            mbar_expect_tx(b, 16384);
            tma_load_h(buf, &tmQ, 0, row + (warp - 10) * 64, b, POL_FIRST);
            tma_load_h(buf + 8192, &tmQ, 64, row + (warp - 10) * 64, b, POL_FIRST);
        }
    }
    if (warp == 0 && lane <= NT) sts(bars + B_ROWS + 4 * lane, lane < NT - 1 ? tile_index(lane, cta) * 128 : -1024);
    if (warp == 1) asm volatile("st.shared.u64 [%0], %1;" ::"r"(bars + B_GO), "l"(go) : "memory");
    __syncthreads();

    if (warp >= 8) {
        asm volatile("setmaxnreg.dec.sync.aligned.u32 24;");
        if (warp == 8) {
            uint32_t ph = 0;
            int slot = 1, s1 = 0, s2 = 0, s3 = 0, flip = 0, nb = 4 * NT, row = (cta >> 3) * 512;
#pragma unroll 1
            for (int n = -1; n <= nb; n++) {
                const int a = n + 2, j = a & 3;
                const bool fst = (first >> (a >> 2)) & 1;
                if (j == 0) {
                    flip = fst ? 0 : flip ^ 1;
                    if (a == 4 * NT - 4) mbar_wait_b(bars + B_DYN, 0);
                    row = lds(bars + B_ROWS + a);
                    if (row < 0) nb = a;
                    if (row & 1) nb = a + 3;
                    row = ((row + 63) >> 10) * 512;
                }
                if (n >= 0) {
                    if (n < nb && ((n & 3) == 3 || ((first >> (n >> 2)) & 1))) { mbar_wait_b(bars + B_KFULL + 8 * s2, (ph >> s2) & 1); ph ^= 1u << s2; }
                    if (n > 0 && ((n & 3) == 0 || ((first >> (n >> 2)) & 1))) { mbar_wait_b(bars + B_VFULL + 8 * s3, (ph >> (s3 + 4)) & 1); ph ^= 16u << s3; }
                    bar_sync(1, 288);
                }
                if (n == 0) bar_arrive(12, 64);
                if (a < nb && (fst || j == 3) && lane == 0) {
                    const uint32_t full = bars + B_KFULL + 8 * slot, buf = sb + SM_K + slot * BLK_BYTES;
                    mbar_expect_tx(full, BLK_BYTES);
                    tma_load_h(buf, &tmK, 0, row + (flip ? 0 : j) * 128, full, POL_NORMAL);
                    tma_load_h(buf + 16384, &tmK, 64, row + (flip ? 0 : j) * 128, full, POL_NORMAL);
                }
                __syncwarp();
                if ((nb & 1) && a + 1 == nb) {
                    mbar_wait_b(bars + B_KFULL + 8 * s1, (ph >> s1) & 1);
                    bar_sync(2, 288);
                    if (lane == 0) {
                        const uint32_t full = bars + B_KFULL + 8 * s2, buf = sb + SM_K + s2 * BLK_BYTES;
                        mbar_expect_tx(full, BLK_BYTES);
                        tma_load(buf, &tmK, 0, row + 384, full);
                        tma_load(buf + 16384, &tmK, 64, row + 384, full);
                    }
                    __syncwarp();
                    mbar_wait_b(bars + B_KFULL + 8 * slot, (ph >> slot) & 1);
                    mbar_wait_b(bars + B_VFULL + 8 * s2, (ph >> (s2 + 4)) & 1);
                    bar_sync(1, 288);
                    if (lane == 0) {
                        const uint32_t full = bars + B_KFULL + 8 * s1, buf = sb + SM_K + s1 * BLK_BYTES;
                        mbar_expect_tx(full, BLK_BYTES);
                        tma_load(buf, &tmV, 0, row + 256, full);
                        tma_load(buf + 16384, &tmV, 64, row + 256, full);
                    }
                    __syncwarp();
                    mbar_wait_b(bars + B_KFULL + 8 * s2, (ph >> s2) & 1);
                    mbar_wait_b(bars + B_VFULL + 8 * s1, (ph >> (s1 + 4)) & 1);
                    bar_sync(2, 288);
                    mbar_wait_b(bars + B_KFULL + 8 * s1, (~ph >> s1) & 1);
                    bar_sync(1, 288);
                    mbar_wait_b(bars + B_VFULL + 8 * slot, (ph >> (slot + 4)) & 1);
                    n = nb;
                }
                if (n >= 0) bar_arrive(2, 288);
                s3 = s2; s2 = s1; s1 = slot;
                if (j != 3 || ((first >> ((a + 1) >> 2)) & 1)) slot = slot == 2 ? 0 : slot + 1;
            }
        } else if (warp == 9) {
            int slot = 0, flip = 0, row = 0, half = 0;
#pragma unroll 1
            for (int a = 0; a < 4 * NT; a++) {
                const int j = a & 3;
                const bool fst = (first >> (a >> 2)) & 1;
                if (j == 0) {
                    flip = fst ? 0 : flip ^ 1;
                    if (a == 4 * NT - 4) mbar_wait_b(bars + B_DYN, 0);
                    row = lds(bars + B_ROWS + a);
                    half = row & 1;
                    row = ((row + 63) >> 10) * 512;
                }
                if (fst || j == 3) {
                    if (a >= 2) bar_sync(8 + (j ^ 2), 160);
                    if (a == 1) bar_sync(12, 64);
                    if (half && j >= 2) { if (j == 3) break; row += 128; }
                    if (row < 0) { if (j == 1) break; }
                    else if (lane == 0) {
                        const uint32_t full = bars + B_VFULL + 8 * slot, buf = sb + SM_V + slot * BLK_BYTES;
                        mbar_expect_tx(full, BLK_BYTES);
                        tma_load_h(buf, &tmV, 0, row + (flip ? 0 : j) * 128, full, POL_NORMAL);
                        tma_load_h(buf + 16384, &tmV, 64, row + (flip ? 0 : j) * 128, full, POL_NORMAL);
                    }
                    if (a >= 4 && a < 4 * NT - 4 && lane == 0 && j == 0) ahead(gv, bars, first, a >> 2, 2);
                    __syncwarp();
                }
                if (j != 3 || ((first >> ((a + 1) >> 2)) & 1)) slot = slot == 2 ? 0 : slot + 1;
            }
        } else {
            const int w = warp - 10;
            const uint32_t buf = sb + SM_Q + w * 16384;
            const uint32_t full = bars + B_QFULL + 24 * w;
            int r0 = 0, r1 = 0, r2 = cta * 128;
#pragma unroll 1
            for (int t = -2;; t++) {
                if (t >= -1) {
                    r0 = r1; r1 = r2; r2 = lds(bars + B_ROWS + 4 * min(t + 2, NT));
                    mbar_wait_b(full + 8, (t + 1) & 1);
                }
                if (t >= 0) {
                    if (r1 < 0) break;
                    if (lane == 0) {
                        asm volatile("fence.proxy.async.shared::cta;" ::: "memory");
                        tma_store_h(buf, &tmO, 0, r0 + w * 64, POL_FIRST);
                        tma_store_h(buf + 8192, &tmO, 64, r0 + w * 64, POL_FIRST);
                        asm volatile("cp.async.bulk.commit_group;" ::: "memory");
                    }
                    if (t == NT - 3) {
                        if (w == 0 && lane == 0) {
                            const uint32_t k = atomicInc(&g_ticket, NCTA - 1);
                            if (k < 2 * NDYN - NFULL) sts(bars + B_ROWS + 4 * (NT - 1), DYN0 * 128 + (k < NFULL ? k * 128 : (k + NFULL) * 64 - 63));
                            mbar_arrive(bars + B_DYN);
                        }
                        __syncwarp();
                        mbar_wait_b(bars + B_DYN, 0);
                        r2 = lds(bars + B_ROWS + 4 * (NT - 1));
                    }
                    asm volatile("cp.async.bulk.wait_group.read 0;" ::: "memory");
                }
                if (r2 >= 0) {
                    if (t >= -1 - w && lane == 0) {
                        mbar_expect_tx(full, 16384);
                        const int r = r2 + ((r2 & 1) ? 63 : w * 64);
                        tma_load_h(buf, &tmQ, 0, r, full, POL_FIRST);
                        tma_load_h(buf + 8192, &tmQ, 64, r, full, POL_FIRST);
                    }
                    __syncwarp();
                    mbar_wait_b(full, t & 1);
                }
                bar_arrive(6 + w, 160);
            }
        }
    } else {
        asm volatile("setmaxnreg.inc.sync.aligned.u32 240;");
        Consumer c;
        c.sb = sb; c.wg = warp >> 2;
        c.zero = __shfl_sync(0xffffffffu, threadIdx.y, 0);
        {
            const int row = (warp & 3) * 16 + (lane & 15);
            c.qaddr = sb + SM_Q + c.wg * 16384 + row * 128 + (((lane >> 4) ^ (row & 7)) << 4);
        }
        if (c.wg == 1) bar_arrive(1, 288);
        c.first = first;
        c.run(gq, gk, gv, go);
    }
}

typedef CUresult (*EncodeFn)(CUtensorMap*, CUtensorMapDataType, cuuint32_t, void*, const cuuint64_t*, const cuuint64_t*,
                             const cuuint32_t*, const cuuint32_t*, CUtensorMapInterleave, CUtensorMapSwizzle,
                             CUtensorMapL2promotion, CUtensorMapFloatOOBfill);

void make_map(EncodeFn enc, CUtensorMap* m, void* p, uint64_t rows, uint32_t box_rows) {
    cuuint64_t dims[2] = {128, rows};
    cuuint64_t strides[1] = {256};
    cuuint32_t box[2] = {64, box_rows};
    cuuint32_t es[2] = {1, 1};
    enc(m, CU_TENSOR_MAP_DATA_TYPE_BFLOAT16, 2, p, dims, strides, box, es, CU_TENSOR_MAP_INTERLEAVE_NONE,
        CU_TENSOR_MAP_SWIZZLE_128B, CU_TENSOR_MAP_L2_PROMOTION_L2_256B, CU_TENSOR_MAP_FLOAT_OOB_FILL_NONE);
}

}

extern "C" void kernel_launch(void* const* d_in, const int* in_sizes, int n_in, void* d_out, int out_size) {
    static EncodeFn enc = nullptr;
    if (!enc) {
        void* fn = nullptr;
        cudaDriverEntryPointQueryResult qr;
        cudaGetDriverEntryPoint("cuTensorMapEncodeTiled", &fn, cudaEnableDefault, &qr);
        enc = (EncodeFn)fn;
        cudaFuncSetAttribute(gqa_fwd_kernel, cudaFuncAttributeMaxDynamicSharedMemorySize, SM_TOTAL);
    }
    CUtensorMap tq, tk, tv, to;
    make_map(enc, &tq, d_in[0], 262144, 64);
    make_map(enc, &tk, d_in[1], 131072, 128);
    make_map(enc, &tv, d_in[2], 131072, 128);
    make_map(enc, &to, d_out, 262144, 64);
    gqa_fwd_kernel<<<NCTA, 384, SM_TOTAL>>>(tq, tk, tv, to, (const char*)d_in[0], (const char*)d_in[1], (const char*)d_in[2], (char*)d_out);
}
```
